```python
import torch

def _softmax(x, axis=-1):
    return torch.softmax(x, dim=axis)
def _gelu(x):
    return torch.nn.functional.gelu(x, approximate="tanh")
def _silu(x):
    return torch.nn.functional.silu(x)
def _sigmoid(x):
    return torch.sigmoid(x)
def _layernorm(x, axis=-1, eps=1e-5):
    m = x.mean(dim=axis, keepdim=True)
    v = x.var(dim=axis, keepdim=True, unbiased=False)
    return (x - m) / torch.sqrt(v + eps)
def _scatter_add(tgt, idx, src, axis=0):
    return tgt.clone().index_add_(axis, idx, src)
def _segment_sum(src, seg, n):
    out = torch.zeros((n,) + src.shape[1:], dtype=src.dtype)
    return out.index_add_(0, seg, src)
def _pad(x, pw):
    flat = tuple(v for pair in reversed(pw) for v in pair)
    return torch.nn.functional.pad(x, flat)

kernel_name = 'standalone__paged_block_table_kv_pagedattention__sampling'

def setup_inputs():

    _w = (lambda a: (lambda t: t.to(torch.bfloat16) if t.is_floating_point() else t)(torch.as_tensor(a)))
    B, Hq, Hkv, Sq, Skv, D = 16, 32, 8, 32, 4096, 128
    bs = 16
    nbps = max(1, Skv // bs)
    num_phys = B * nbps + 4
    bt = torch.randperm(num_phys)[: B * nbps].reshape(B, nbps).to(torch.int64)
    cl = (nbps * bs - (torch.arange(1, B + 1, dtype=torch.int64) * 2654435761) % max(1, nbps * bs // 2)).to(torch.int64)
    return {
        "q": _w((lambda *s: torch.randn(*s, dtype=torch.bfloat16) * 0.8)(B, Hq, Sq, D)),
        "k_cache": _w((lambda *s: torch.randn(*s, dtype=torch.bfloat16) * 0.8)(num_phys, bs, Hkv, D)),
        "v_cache": _w((lambda *s: torch.randn(*s, dtype=torch.bfloat16) * 0.05)(num_phys, bs, Hkv, D)),
        "block_table": _w(bt),
        "context_lens": _w(cl),
    }

def reference(q, k_cache, v_cache, block_table, context_lens):
    B, Hq, Sq, D = q.shape
    bs = k_cache.shape[1]
    Hkv = k_cache.shape[2]
    nbps = block_table.shape[1]
    Skv = nbps * bs
    bt = block_table.reshape(-1)
    k = (lambda x, *d: x.permute(*d))(k_cache[bt].reshape(B, Skv, Hkv, D), 0, 2, 1, 3)
    v = (lambda x, *d: x.permute(*d))(v_cache[bt].reshape(B, Skv, Hkv, D), 0, 2, 1, 3)
    g = Hq // Hkv
    qg = q.reshape(B, Hkv, g, Sq, D)
    scores = torch.einsum("bhgqd,bhkd->bhgqk", qg, k) * (D ** -0.5)
    pos = torch.arange(Skv)
    msk = pos[None, :] < context_lens[:, None]
    scores = torch.where(msk[:, None, None, None, :], scores, -1e9)
    p = _softmax(scores, axis=-1)
    out = torch.einsum("bhgqk,bhkd->bhgqd", p, v)
    return out.reshape(B, Hq, Sq, D)
```

```cpp
#include <cuda_runtime.h>
#include <cuda.h>
#include <cuda_bf16.h>
#include <stdint.h>

namespace {

constexpr int kB = 16, kHkv = 8, kD = 128, kPage = 16, kNBPS = 256;
constexpr int kRows = 128;
constexpr int kSkv = kNBPS * kPage;
constexpr int kTileN = 64;
constexpr int kSlotBytes = 16384;
constexpr int kStages = 6;
constexpr float kDramEfficiency = 0.972f;
constexpr float kWindow = 1600.f;
constexpr float kTaper = 750.f;
constexpr float kTaperSpan = 8000.f;
constexpr float kStartLag = 600.f;
constexpr float kClockGain = 0.2f;
constexpr float kClockStep = 800.f;
constexpr unsigned kClockWarmup = 200;
constexpr int kEvenTiles = 4;
constexpr int kQPrefetch = 16384;
constexpr float kMaxGrowth = 4096.f;
constexpr int kThreads = 384;

constexpr int kSmemRing = kStages * 2 * kSlotBytes;
constexpr int kSortWords = 160;
constexpr int kSmemHead = 4096;
constexpr int kSmemBytes = 1024 + kSmemHead + kSmemRing;

__device__ __forceinline__ uint32_t smem_u32(const void* p) {
    return (uint32_t)__cvta_generic_to_shared(p);
}
__device__ __forceinline__ void mbar_init(uint32_t bar, uint32_t cnt) {
    asm volatile("mbarrier.init.shared::cta.b64 [%0], %1;" ::"r"(bar), "r"(cnt) : "memory");
}
__device__ __forceinline__ void mbar_expect_tx(uint32_t bar, uint32_t bytes) {
    asm volatile("mbarrier.arrive.expect_tx.shared::cta.b64 _, [%0], %1;" ::"r"(bar), "r"(bytes) : "memory");
}
__device__ __forceinline__ void mbar_arrive_if(uint32_t bar, bool pred) {
    asm volatile("{\n.reg .pred p;\nsetp.ne.u32 p, %1, 0;\n@p mbarrier.arrive.shared::cta.b64 _, [%0];\n}"
                 ::"r"(bar), "r"((uint32_t)pred) : "memory");
}
__device__ __forceinline__ void mbar_wait(uint32_t bar, uint32_t parity) {
    asm volatile(
        "{\n.reg .pred p;\n"
        "WAIT_LOOP:\n"
        "mbarrier.try_wait.parity.shared::cta.b64 p, [%0], %1;\n"
        "@p bra WAIT_DONE;\n"
        "bra WAIT_LOOP;\n"
        "WAIT_DONE:\n}" ::"r"(bar), "r"(parity) : "memory");
}
__device__ __forceinline__ void tma_page(uint32_t dst, const CUtensorMap* tm, uint32_t bar, int c2, int c3, uint64_t pol) {
    asm volatile(
        "cp.async.bulk.tensor.4d.shared::cluster.global.mbarrier::complete_tx::bytes.L2::cache_hint"
        " [%0], [%1, {%3, %3, %4, %5}], [%2], %6;"
        ::"r"(dst), "l"(tm), "r"(bar), "r"(0), "r"(c2), "r"(c3), "l"(pol) : "memory");
}
__device__ __forceinline__ void tma_group(uint32_t dst, const CUtensorMap* tm, uint32_t bar, int c1, int c2, int c3, uint64_t pol) {
    asm volatile(
        "cp.async.bulk.tensor.4d.shared::cluster.global.mbarrier::complete_tx::bytes.L2::cache_hint"
        " [%0], [%1, {%3, %4, %5, %6}], [%2], %7;"
        ::"r"(dst), "l"(tm), "r"(bar), "r"(0), "r"(c1), "r"(c2), "r"(c3), "l"(pol) : "memory");
}
__device__ __forceinline__ void tma_2d(uint32_t dst, const CUtensorMap* tm, uint32_t bar, int c0, int c1) {
    asm volatile(
        "cp.async.bulk.tensor.2d.shared::cluster.global.mbarrier::complete_tx::bytes"
        " [%0], [%1, {%3, %4}], [%2];" ::"r"(dst), "l"(tm), "r"(bar), "r"(c0), "r"(c1)
        : "memory");
}
__device__ __forceinline__ int4 ldg_v4(const int4* p) {
    int4 v;
    asm volatile("ld.global.nc.v4.b32 {%0, %1, %2, %3}, [%4];" : "=r"(v.x), "=r"(v.y), "=r"(v.z), "=r"(v.w) : "l"(p) : "memory");
    return v;
}
__device__ __forceinline__ bool elect_one() {
    uint32_t pred;
    asm volatile("{\n.reg .pred p;\nelect.sync _|p, 0xffffffff;\nselp.u32 %0, 1, 0, p;\n}" : "=r"(pred));
    return pred;
}
__device__ __forceinline__ void wgmma_fence() { asm volatile("wgmma.fence.sync.aligned;" ::: "memory"); }
__device__ __forceinline__ void wgmma_commit() { asm volatile("wgmma.commit_group.sync.aligned;" ::: "memory"); }
template <int N>
__device__ __forceinline__ void wgmma_wait() { asm volatile("wgmma.wait_group.sync.aligned %0;" ::"n"(N) : "memory"); }
template <int N>
__device__ __forceinline__ void fence_regs(float (&r)[N]) {
#pragma unroll
    for (int i = 0; i < N; i++) asm volatile("" : "+f"(r[i])::"memory");
}
template <int N>
__device__ __forceinline__ void fence_regs(uint32_t (&r)[N]) {
#pragma unroll
    for (int i = 0; i < N; i++) asm volatile("" : "+r"(r[i])::"memory");
}
__device__ __forceinline__ float ex2(float x) {
    float y;
    asm("ex2.approx.ftz.f32 %0, %1;" : "=f"(y) : "f"(x));
    return y;
}
__device__ __forceinline__ uint32_t pack_bf16(float lo, float hi) {
    uint32_t r;
    asm("cvt.rn.bf16x2.f32 %0, %1, %2;" : "=r"(r) : "f"(hi), "f"(lo));
    return r;
}

template <int TB>
__device__ __forceinline__ void wgmma_n64(float (&d)[32], const uint32_t* a, uint32_t desc_lo, uint32_t desc_hi, int scale_d) {
    asm volatile(
        "{\n.reg .pred p;\n.reg .b64 db;\n"
        "setp.ne.b32 p, %38, 0;\n"
        "mov.b64 db, {%36, %37};\n"
        "wgmma.mma_async.sync.aligned.m64n64k16.f32.bf16.bf16 "
        "{%0, %1, %2, %3, %4, %5, %6, %7, %8, %9, %10, %11, %12, %13, %14, %15, "
        "%16, %17, %18, %19, %20, %21, %22, %23, %24, %25, %26, %27, %28, %29, %30, %31}, "
        "{%32, %33, %34, %35}, db, p, 1, 1, %39;\n}"
        : "+f"(d[0]), "+f"(d[1]), "+f"(d[2]), "+f"(d[3]), "+f"(d[4]), "+f"(d[5]), "+f"(d[6]), "+f"(d[7]),
          "+f"(d[8]), "+f"(d[9]), "+f"(d[10]), "+f"(d[11]), "+f"(d[12]), "+f"(d[13]), "+f"(d[14]), "+f"(d[15]),
          "+f"(d[16]), "+f"(d[17]), "+f"(d[18]), "+f"(d[19]), "+f"(d[20]), "+f"(d[21]), "+f"(d[22]), "+f"(d[23]),
          "+f"(d[24]), "+f"(d[25]), "+f"(d[26]), "+f"(d[27]), "+f"(d[28]), "+f"(d[29]), "+f"(d[30]), "+f"(d[31])
        : "r"(a[0]), "r"(a[1]), "r"(a[2]), "r"(a[3]), "r"(desc_lo), "r"(desc_hi), "r"(scale_d), "n"(TB));
}
__device__ __forceinline__ void wgmma_pv(float (&d)[64], const uint32_t* a, uint32_t desc_lo, uint32_t desc_hi, int scale_d) {
    asm volatile(
        "{\n.reg .pred p;\n.reg .b64 db;\n"
        "setp.ne.b32 p, %70, 0;\n"
        "mov.b64 db, {%68, %69};\n"
        "wgmma.mma_async.sync.aligned.m64n128k16.f32.bf16.bf16 "
        "{%0, %1, %2, %3, %4, %5, %6, %7, %8, %9, %10, %11, %12, %13, %14, %15, "
        "%16, %17, %18, %19, %20, %21, %22, %23, %24, %25, %26, %27, %28, %29, %30, %31, "
        "%32, %33, %34, %35, %36, %37, %38, %39, %40, %41, %42, %43, %44, %45, %46, %47, "
        "%48, %49, %50, %51, %52, %53, %54, %55, %56, %57, %58, %59, %60, %61, %62, %63}, "
        "{%64, %65, %66, %67}, db, p, 1, 1, 1;\n}"
        : "+f"(d[0]), "+f"(d[1]), "+f"(d[2]), "+f"(d[3]), "+f"(d[4]), "+f"(d[5]), "+f"(d[6]), "+f"(d[7]),
          "+f"(d[8]), "+f"(d[9]), "+f"(d[10]), "+f"(d[11]), "+f"(d[12]), "+f"(d[13]), "+f"(d[14]), "+f"(d[15]),
          "+f"(d[16]), "+f"(d[17]), "+f"(d[18]), "+f"(d[19]), "+f"(d[20]), "+f"(d[21]), "+f"(d[22]), "+f"(d[23]),
          "+f"(d[24]), "+f"(d[25]), "+f"(d[26]), "+f"(d[27]), "+f"(d[28]), "+f"(d[29]), "+f"(d[30]), "+f"(d[31]),
          "+f"(d[32]), "+f"(d[33]), "+f"(d[34]), "+f"(d[35]), "+f"(d[36]), "+f"(d[37]), "+f"(d[38]), "+f"(d[39]),
          "+f"(d[40]), "+f"(d[41]), "+f"(d[42]), "+f"(d[43]), "+f"(d[44]), "+f"(d[45]), "+f"(d[46]), "+f"(d[47]),
          "+f"(d[48]), "+f"(d[49]), "+f"(d[50]), "+f"(d[51]), "+f"(d[52]), "+f"(d[53]), "+f"(d[54]), "+f"(d[55]),
          "+f"(d[56]), "+f"(d[57]), "+f"(d[58]), "+f"(d[59]), "+f"(d[60]), "+f"(d[61]), "+f"(d[62]), "+f"(d[63])
        : "r"(a[0]), "r"(a[1]), "r"(a[2]), "r"(a[3]), "r"(desc_lo), "r"(desc_hi), "r"(scale_d));
}

__device__ __forceinline__ int bcast(int v, int lane, int src) {
    return __reduce_max_sync(~0u, lane == src ? v : 0);
}

__device__ __forceinline__ void sort_pages(const int4& row0, const int4& row1, int first, int n, int lane,
                                           uint32_t s_list, uint32_t s_bits) {
    constexpr int kW = kSortWords / 32;
    const uint32_t e[8] = {(uint32_t)row0.x, (uint32_t)row0.y, (uint32_t)row0.z, (uint32_t)row0.w,
                           (uint32_t)row1.x, (uint32_t)row1.y, (uint32_t)row1.z, (uint32_t)row1.w};
    uint32_t wa[8];
#pragma unroll
    for (int i = 0; i < 8; i++) {
        const bool use = (unsigned)(lane - first + (i >> 2) * 32) < (unsigned)n && e[i] < kSortWords * 32;
        wa[i] = s_bits + (use ? e[i] >> 5 : 0) * 8;
        asm volatile("{\n.reg .pred p;\nsetp.ne.u32 p, %2, 0;\n@p red.shared.or.b32 [%0], %1;\n}"
                     ::"r"(wa[i]), "r"(1u << (e[i] & 31)), "r"((uint32_t)use) : "memory");
    }
    __syncwarp();
    uint32_t cnt[kW + 1];
    cnt[0] = 0;
#pragma unroll
    for (int i = 0; i < kW; i++) {
        uint32_t w;
        asm volatile("ld.shared.b32 %0, [%1];" : "=r"(w) : "r"(s_bits + (lane * kW + i) * 8) : "memory");
        cnt[i + 1] = cnt[i] + __popc(w);
    }
    uint32_t scan = cnt[kW];
#pragma unroll
    for (int o = 1; o < 32; o <<= 1) {
        const uint32_t v = __shfl_up_sync(~0u, scan, o);
        if (lane >= o) scan += v;
    }
    const bool sorted = __shfl_sync(~0u, scan, 31) == (uint32_t)n * 4;
#pragma unroll
    for (int i = 0; i < kW; i++)
        asm volatile("st.shared.b32 [%0], %1;" ::"r"(s_bits + (lane * kW + i) * 8 + 4), "r"(scan - cnt[kW] + cnt[i]) : "memory");
    __syncwarp();
#pragma unroll
    for (int i = 0; i < 8; i++) {
        uint32_t w, base;
        asm volatile("ld.shared.v2.b32 {%0, %1}, [%2];" : "=r"(w), "=r"(base) : "r"(wa[i]) : "memory");
        wa[i] = base + __popc(w & ((1u << (e[i] & 31)) - 1));
    }
#pragma unroll
    for (int i = 0; i < 8; i++) {
        const uint32_t pos = sorted ? wa[i] : (lane - first) * 4 + (i >> 2) * 128 + (i & 3);
        asm volatile("{\n.reg .pred p;\nsetp.ne.u32 p, %2, 0;\n@p st.shared.b32 [%0], %1;\n}"
                     ::"r"(s_list + pos * 4), "r"(e[i] * 2), "r"((uint32_t)((unsigned)(lane - first + (i >> 2) * 32) < (unsigned)n)) : "memory");
    }
}

__device__ unsigned g_progress;

struct Maps {
    CUtensorMap page[2];
    CUtensorMap group[2];
    CUtensorMap vhalf;
    CUtensorMap q;
};

struct Ring {
    int slot;
    uint32_t phase;
    __device__ __forceinline__ void advance() {
        if (++slot == kStages) { slot = 0; phase ^= 1; }
    }
};

__global__ void __launch_bounds__(kThreads, 1)
paged_attn_kernel(const int* __restrict__ ctx, const int* __restrict__ table, const __nv_bfloat16* __restrict__ q,
                  __nv_bfloat16* __restrict__ out, unsigned* progress, int oob_coord, float tile_ns,
                  const __grid_constant__ Maps tm) {
    extern __shared__ uint8_t smem_raw[];
    const int tid = threadIdx.x, lane = tid & 31;
    const int b = blockIdx.x / kHkv, h = blockIdx.x % kHkv;
    const int bh = b * kHkv + h;
    const __nv_bfloat16* q_tile = q + (size_t)bh * kRows * kD;
    if (elect_one()) asm volatile("cp.async.bulk.prefetch.L2.global [%0], %1;" ::"l"(q_tile), "r"(16) : "memory");
    if (tid == 0) asm volatile("cp.async.bulk.prefetch.L2.global [%0], %1;" ::"l"(q_tile), "r"(kQPrefetch) : "memory");
    uint32_t t_begin;
    asm volatile("mov.u32 %0, %globaltimer_lo;" : "=r"(t_begin) :: "memory");
    int cl;
    int4 row0, row1;
    if (tid >= 256) {
        const bool head = tid >> 5 == 10;
        const int4* row = reinterpret_cast<const int4*>(table + b * kNBPS) + (head ? 0 : lane);
        row0 = ldg_v4(row);
        asm volatile("ld.global.nc.b32 %0, [%1];" : "=r"(cl) : "l"(ctx + (lane & (kB - 1))) : "memory");
        row1 = ldg_v4(row + (head ? 0 : 32));
    }
    const int warp = __shfl_sync(~0u, tid >> 5, 0);
    const uint32_t sbase = __reduce_max_sync(~0u, (smem_u32(smem_raw) + 1023 + kSmemHead) & ~1023u);
    const uint32_t s_bits = sbase - 4096, s_list = sbase - 2048;
    const uint32_t s_bar = sbase - 1024, s_clock = sbase - 512;
    const uint32_t s_bar_last = s_bar + 32 * kStages;
    static_assert(kStages < 8, "barrier layout");

    if (warp < 8) {
        if (warp <= kStages && elect_one()) {
            mbar_init(s_bar + 32 * warp, 1);
            mbar_init(s_bar + 32 * warp + 8, 1);
            mbar_init(s_bar + 32 * warp + 16, 9);
            mbar_init(s_bar + 32 * warp + 24, 8);
            asm volatile("fence.mbarrier_init.release.cluster;" ::: "memory");
            if (warp < 2 || warp == kStages) {
                mbar_expect_tx(s_bar + 32 * warp, warp < 2 ? kSlotBytes : kSlotBytes / 2);
                mbar_expect_tx(s_bar + 32 * warp + 8, warp < 2 ? kSlotBytes : kSlotBytes / 2);
            }
            if (warp == 0) {
                asm volatile("fence.proxy.async.shared::cta;" ::: "memory");
                tma_2d(sbase, &tm.q, s_bar, 0, bh * kRows);
                tma_2d(sbase + kSlotBytes, &tm.q, s_bar + 8, 64, bh * kRows);
            }
        }
    } else if (warp == 8) {
#pragma unroll
        for (int i = 0; i < kSortWords / 32; i++)
            asm volatile("st.shared.b32 [%0], %1;" ::"r"(s_bits + (lane * (kSortWords / 32) + i) * 8), "r"(0) : "memory");
    }
    __syncthreads();

    if (warp >= 8) {
        asm volatile("setmaxnreg.dec.sync.aligned.u32 56;");
        const int kv = (warp >> 1) & 1;
        uint64_t pol;
        asm volatile("createpolicy.fractional.L2::evict_first.b64 %0, 1.0;" : "=l"(pol));
        const int len_l = cl <= 0 ? kSkv : min(cl, kSkv);
        const int len = bcast(len_l, lane, b);
        const int top = (len - 1) / kTileN;
        const int n = max(top, 2);
        const int early = top > 3;
        if (warp == 10 && early && elect_one()) {
#pragma unroll
            for (int i = 0; i < 2; i++) {
                const uint32_t dst = sbase + (4 + i) * kSlotBytes, bar = s_bar + 64 + 8 * i;
                mbar_expect_tx(bar, kSlotBytes);
                tma_page(dst, &tm.page[i], bar, h * 2, row0.x * 2, pol);
                tma_page(dst + 4096, &tm.page[i], bar, h * 2, row0.y * 2, pol);
                tma_page(dst + 8192, &tm.page[i], bar, h * 2, row0.z * 2, pol);
                tma_page(dst + 12288, &tm.page[i], bar, h * 2, row0.w * 2, pol);
            }
        }
        if (warp & 1) {
            const int4 src = top < 32 ? row0 : row1;
            const int p0 = bcast(src.x, lane, top & 31) * 2, p1 = bcast(src.y, lane, top & 31) * 2;
            const int p2 = bcast(src.z, lane, top & 31) * 2, p3 = bcast(src.w, lane, top & 31) * 2;
            const int rem = len - top * kTileN, full = (rem - 1) / kPage, r = rem - full * kPage;
            const int last = full == 0 ? p0 : full == 1 ? p1 : full == 2 ? p2 : p3;
            const uint32_t off = (3 - full) * 4096;
            if (elect_one()) {
                const uint32_t dst = sbase + (2 + kv) * kSlotBytes, bar = s_bar + 32 + 8 * kv;
                tma_page(dst + ((off + 4096) & 0x3fff), &tm.page[kv], bar, h * 2, full > 0 ? p0 : oob_coord, pol);
                tma_page(dst + ((off + 8192) & 0x3fff), &tm.page[kv], bar, h * 2, full > 1 ? p1 : oob_coord, pol);
                tma_page(dst + ((off + 12288) & 0x3fff), &tm.page[kv], bar, h * 2, full > 2 ? p2 : oob_coord, pol);
                tma_group(dst + off, &tm.group[kv], bar, r - 16, h * 2, last + 1, pol);
                tma_group(dst + off + 2048, &tm.group[kv], bar, min(r - 8, 0), h * 2, last, pol);
                asm volatile("prefetch.tensormap [%0];" ::"l"(&tm.vhalf) : "memory");
            }
            return;
        }
        const int full_l = lane < kB ? (len_l - 1) / kTileN : 0;
        const float t_all = (float)(__reduce_add_sync(~0u, full_l) * kHkv) * tile_ns;
        float origin = (kB * kHkv + __reduce_add_sync(~0u, lane < kB ? len_l - full_l * kTileN : 0) * (1.f / 8)) * tile_ns + kStartLag;
        if (warp == 10) {
            if (lane == 0) {
                const float gain = fminf(__fdividef(kClockGain * t_all, (float)(n * kB * kHkv) * tile_ns), 0.5f);
                mbar_arrive_if(s_bar + 16, true);
                mbar_arrive_if(s_bar + 48, true);
                Ring m{2, 0};
                unsigned g;
#pragma unroll 1
                for (int t = n - 1; t >= 2; t--) {
                    mbar_wait(s_bar + 32 * m.slot, m.phase);
                    mbar_arrive_if(s_bar + 32 * m.slot + 16, true);
                    m.advance();
                    uint32_t now;
                    asm volatile("mov.u32 %0, %globaltimer_lo;" : "=r"(now) :: "memory");
                    asm volatile("atom.relaxed.gpu.global.add.u32 %0, [%1], 1;" : "=r"(g) : "l"(progress) : "memory");
                    g &= 0xfffff;
                    const float d = (float)(int)(now - t_begin) - (float)g * tile_ns - origin;
                    if (g >= kClockWarmup) origin = fmaf(fminf(d, kClockStep), gain, origin);
                    asm volatile("st.volatile.shared.b32 [%0], %1;" ::"r"(s_clock), "r"(t_begin + (int)origin) : "memory");
                }
                asm volatile("atom.relaxed.gpu.global.add.u32 %0, [%1], 0x100000;" : "=r"(g) : "l"(progress) : "memory");
                if ((g >> 20) == kB * kHkv - 1) asm volatile("st.relaxed.gpu.global.u32 [%0], 0;" ::"l"(progress) : "memory");
            }
            return;
        }
        asm volatile("st.volatile.shared.b32 [%0], %1;" ::"r"(s_clock), "r"(t_begin + (int)origin) : "memory");
        if (lane < 8) asm volatile("st.shared.b32 [%0], %1;" ::"r"(s_list + lane * 4), "r"(oob_coord) : "memory");
        sort_pages(row0, row1, early, top - early, lane, s_list, s_bits);
        __syncwarp();
        auto pages = [&](int t) {
            int4 pg;
            asm volatile("ld.shared.v4.b32 {%0, %1, %2, %3}, [%4];" : "=r"(pg.x), "=r"(pg.y), "=r"(pg.z), "=r"(pg.w)
                         : "r"(s_list + t * 16) : "memory");
            return pg;
        };
        const float dt_end = tile_ns * (kB * kHkv / 2);
        const float dt = __fdividef(t_all - dt_end * (2 * kEvenTiles), (float)(2 * max(n - kEvenTiles, 1)));
        const float stagger = dt_end * ((b * 7 % kB) + 0.5f) * (1.f / kB);
        float left = (n > kEvenTiles ? t_all : dt_end * (float)(2 * n)) - stagger;
        auto wait_due = [&](float step) {
            const int due = (int)(t_all - kWindow - left + fmaxf(fmaf(left, -kTaper / kTaperSpan, kTaper), 0.f));
            left -= step;
#pragma unroll 1
            while (true) {
                uint32_t now, org;
                asm volatile("ld.volatile.shared.b32 %0, [%1];" : "=r"(org) : "r"(s_clock) : "memory");
                asm volatile("mov.u32 %0, %globaltimer_lo;" : "=r"(now));
                const int wait = due - (int)(now - org);
                if (wait <= 0) break;
                if (wait > 64) __nanosleep(min(wait >> 1, 200));
            }
        };
        auto acquire = [&](const Ring& r, int kv, float step) {
            const uint32_t bar = s_bar + 32 * r.slot + 8 * kv;
            mbar_wait(bar + 16, r.phase ^ 1);
            if (lane == 0) mbar_expect_tx(bar, kSlotBytes);
            wait_due(step);
            return bar;
        };
        auto load4 = [&](uint32_t dst, uint32_t stride, const CUtensorMap* map, uint32_t bar, int c2, const int4& pg) {
            if (elect_one()) {
                tma_page(dst, map, bar, c2, pg.x, pol);
                tma_page(dst + stride, map, bar, c2, pg.y, pol);
                tma_page(dst + 2 * stride, map, bar, c2, pg.z, pol);
                tma_page(dst + 3 * stride, map, bar, c2, pg.w, pol);
            }
        };
        Ring r{2 + early, 0};
        if (early) left -= 2.f * (n > kEvenTiles ? dt : dt_end);
#pragma unroll 1
        for (int t = n - 1 - early; t >= 3; t--) {
            const int4 pg = pages(t);
            const uint32_t dst = sbase + 2 * r.slot * kSlotBytes;
            const float step = t < kEvenTiles ? dt_end : dt;
            load4(dst, 4096, &tm.page[0], acquire(r, 0, step), h * 2, pg);
            load4(dst + kSlotBytes, 4096, &tm.page[1], acquire(r, 1, step), h * 2, pg);
            r.advance();
        }
        Ring rv = r;
#pragma unroll 1
        for (int i = n > 2 ? 0 : 1; i < (n > 2 ? 4 : 3); i++) {
            const int kv = i == 3;
            const int4 pg = pages(kv ? 2 : 2 - i);
            const Ring cur = kv ? rv : r;
            load4(sbase + (2 * cur.slot + kv) * kSlotBytes, 4096, &tm.page[kv],
                  acquire(cur, kv, dt_end), h * 2, pg);
            if (kv) rv.advance(); else r.advance();
        }
        left += 0.5f * stagger;
#pragma unroll 1
        for (int i = 0; i < 4; i++) {
            const int half = i >> 1;
            const int4 pg = pages(~i & 1);
            uint32_t bar = s_bar_last + 8 * half;
            if (!(i & 1)) {
                bar = s_bar + 32 * rv.slot + 8;
                mbar_wait(bar + 16, rv.phase ^ 1);
                if (lane == 0) mbar_expect_tx(bar, kSlotBytes / 2);
            }
            wait_due(0.5f * dt_end);
            load4(sbase + (2 * rv.slot + 1) * kSlotBytes + (i & 1) * 8192, 2048, &tm.vhalf, bar, h * 2 + half, pg);
            if (i & 1) rv.advance();
        }
    } else {
        asm volatile("setmaxnreg.inc.sync.aligned.u32 224;");
        const int wg = warp >> 2;
        const int clb = __reduce_max_sync(~0u, __ldg(ctx + b));
        const int len = clb <= 0 ? kSkv : min(clb, kSkv);
        const int top = (len - 1) / kTileN;
        const float c = clb <= 0 ? 0.f : 0.08838834764831845f * 1.4426950408889634f;

        if (wg == 1) asm volatile("bar.arrive 4, 256;" ::: "memory");
        constexpr uint32_t kDescHi = (2048u >> 4) | (1u << 30);
        constexpr uint32_t kLboK = 1u << 16, kLboV = (1024u >> 4) << 16;
        const uint32_t desc_base = (sbase & 0x3FFFF) >> 4;

        const uint32_t stg = sbase + (max(top, 2) + 3) % kStages * 2 * kSlotBytes + warp * 4096;
        const uint32_t st_addr = __shfl_sync(~0u, stg + (lane & 15) * 128 + (((lane >> 4) ^ (lane & 7)) << 4), lane);
        const uint32_t ld_addr = __shfl_sync(~0u, stg + (lane >> 3) * 128 + (((lane & 7) ^ (lane >> 3)) << 4), lane);
        const uint32_t out_off = __shfl_sync(~0u, ((bh * kRows + warp * 16 + (lane >> 3)) * kD + (lane & 7) * 8) * 2, lane);
        float o[64], s[32];
        uint32_t qf[32], p[16];
#pragma unroll
        for (int i = 0; i < 16; i++) p[i] = 0;
#pragma unroll
        for (int i = 0; i < 64; i++) o[i] = 0.f;
#pragma unroll
        for (int i = 0; i < 32; i++) asm volatile("" : "=f"(s[i]));
        float m0 = -1e30f, m1 = -1e30f, n0 = -m0 * c, n1 = n0, l0 = 0.f, l1 = 0.f;
        {
            const int row = wg * 64 + (warp & 3) * 16 + (lane & 7) + ((lane >> 3) & 1) * 8;
#pragma unroll
            for (int half = 0; half < 2; half++) {
                mbar_wait(s_bar + 8 * half, 0);
                const uint32_t base = sbase + half * kSlotBytes + row * 128;
#pragma unroll
                for (int ks = 0; ks < 4; ks++) {
                    const uint32_t addr = base + (((ks * 2 + (lane >> 4)) ^ (lane & 7)) << 4);
                    uint32_t* f = qf + (half * 4 + ks) * 4;
                    asm volatile("ldmatrix.sync.aligned.m8n8.x4.shared.b16 {%0, %1, %2, %3}, [%4];"
                                 : "=r"(f[0]), "=r"(f[1]), "=r"(f[2]), "=r"(f[3]) : "r"(addr) : "memory");
                }
            }
            __syncwarp();
            mbar_arrive_if(s_bar + 16, lane == 0);
        }

        float w0, w1;
        auto exps = [&](uint32_t (&p)[16]) {
            float v0, v1;
#pragma unroll
            for (int i = 0; i < 8; i++) {
                const float e0 = ex2(fmaf(s[4 * i], c, n0)), e1 = ex2(fmaf(s[4 * i + 1], c, n0));
                const float e2 = ex2(fmaf(s[4 * i + 2], c, n1)), e3 = ex2(fmaf(s[4 * i + 3], c, n1));
                w0 = i ? w0 + e0 : e0;
                v0 = i ? v0 + e1 : e1;
                w1 = i ? w1 + e2 : e2;
                v1 = i ? v1 + e3 : e3;
                p[2 * i] = pack_bf16(e0, e1);
                p[2 * i + 1] = pack_bf16(e2, e3);
            }
            w0 += v0;
            w1 += v1;
        };
        auto must_redo = [&](int skip) { return __any_sync(~0u, fmaxf(w0, w1) > kMaxGrowth || skip > 0); };
        auto redo = [&](int skip, uint32_t (&p)[16], auto&& rescale_pending) {
            const int col = (lane & 3) * 2;
            float x0 = m0, x1 = m1;
#pragma unroll
            for (int i = 0; i < 8; i++) {
                if (i * 8 + col < skip) { s[4 * i] = -INFINITY; s[4 * i + 2] = -INFINITY; }
                if (i * 8 + col + 1 < skip) { s[4 * i + 1] = -INFINITY; s[4 * i + 3] = -INFINITY; }
                x0 = fmaxf(x0, fmaxf(s[4 * i], s[4 * i + 1]));
                x1 = fmaxf(x1, fmaxf(s[4 * i + 2], s[4 * i + 3]));
            }
            x0 = fmaxf(x0, __shfl_xor_sync(~0u, x0, 1));
            x1 = fmaxf(x1, __shfl_xor_sync(~0u, x1, 1));
            x0 = fmaxf(x0, __shfl_xor_sync(~0u, x0, 2));
            x1 = fmaxf(x1, __shfl_xor_sync(~0u, x1, 2));
            const float a0 = ex2((m0 - x0) * c), a1 = ex2((m1 - x1) * c);
            m0 = x0;
            m1 = x1;
            n0 = -x0 * c;
            n1 = -x1 * c;
            l0 *= a0;
            l1 *= a1;
#pragma unroll
            for (int i = 0; i < 16; i++) {
                o[4 * i] *= a0;
                o[4 * i + 1] *= a0;
                o[4 * i + 2] *= a1;
                o[4 * i + 3] *= a1;
                rescale_pending(i, i & 1 ? a1 : a0);
            }
            exps(p);
        };
        auto issue_qk = [&](int slot) {
            const uint32_t lo = desc_base + kLboK + slot * (2 * kSlotBytes >> 4);
#pragma unroll
            for (int ks = 0; ks < 8; ks++)
                wgmma_n64<0>(s, qf + ks * 4, lo + (ks >> 2) * 64 + (ks & 3) * 2, kDescHi, ks != 0);
        };
        auto issue_pv = [&](int slot) {
            const uint32_t lo = desc_base + kLboV + (kSlotBytes >> 4) + slot * (2 * kSlotBytes >> 4);
#pragma unroll
            for (int ks = 0; ks < 4; ks++) wgmma_pv(o, p + ks * 4, lo + ks * 256, kDescHi, 1);
        };
        auto turn_begin = [&]() {
            asm volatile("bar.sync %0, 256;" ::"r"(4 + wg) : "memory");
        };
        auto turn_end = [&]() {
            asm volatile("bar.arrive %0, 256;" ::"r"(5 - wg) : "memory");
        };

        Ring rv{0, 0}, r{1, 0};
        int skip = (top + 1) * kTileN - len;
        int t = max(top, 2);
        fence_regs(qf);
#pragma unroll 1
        do {
            const uint32_t bar_v = s_bar + 32 * rv.slot + 8, bar_k = s_bar + 32 * r.slot;
            fence_regs(s);
            fence_regs(o);
            fence_regs(p);
            mbar_wait(bar_v, rv.phase);
            turn_begin();
            wgmma_fence();
            issue_pv(rv.slot);
            wgmma_commit();
            mbar_wait(bar_k, r.phase);
            wgmma_fence();
            issue_qk(r.slot);
            wgmma_commit();
            turn_end();
            rv = r;
            r.advance();
            wgmma_wait<0>();
            fence_regs(s);
            fence_regs(o);
            fence_regs(p);
            mbar_arrive_if(bar_k + 16, lane == 0);
            mbar_arrive_if(bar_v + 16, lane == 1);
            exps(p);
            if (must_redo(skip)) redo(skip, p, [](int, float) {});
            skip = 0;
            l0 += w0;
            l1 += w1;
        } while (--t >= 2);
        uint32_t p1[16], p0[16];
#pragma unroll
        for (int i = 0; i < 16; i++) p0[i] = 0;
#pragma unroll
        for (t = 1; t >= 0; t--) {
            fence_regs(s);
            turn_begin();
            mbar_wait(s_bar + 32 * r.slot, r.phase);
            wgmma_fence();
            issue_qk(r.slot);
            wgmma_commit();
            turn_end();
            r.advance();
#pragma unroll
            for (int i = 0; i < 16; i++) p1[i] = p0[i];
            wgmma_wait<0>();
            fence_regs(s);
            exps(p0);
            if (must_redo(top <= t))
                redo(top <= t ? kTileN : 0, p0, [&](int i, float a) {
                    p[i] = pack_bf16(__uint_as_float(p[i] << 16) * a, __uint_as_float(p[i] & 0xffff0000u) * a);
                    p1[i] = pack_bf16(__uint_as_float(p1[i] << 16) * a, __uint_as_float(p1[i] & 0xffff0000u) * a);
                });
            l0 += w0;
            l1 += w1;
        }
        fence_regs(o);
        fence_regs(p);
        fence_regs(p1);
        fence_regs(p0);
        char* dst = reinterpret_cast<char*>(out) + out_off;
        auto pv_half = [&](int half, const Ring& rv, float (&d)[32]) {
            const uint32_t lo = desc_base + (kSlotBytes >> 4) + rv.slot * (2 * kSlotBytes >> 4);
            mbar_wait(s_bar + 32 * rv.slot + 8, rv.phase);
            turn_begin();
            wgmma_fence();
#pragma unroll
            for (int ks = 0; ks < 4; ks++)
                wgmma_n64<1>(d, p1 + ks * 4, lo + ks * 128, (1024u >> 4) | (1u << 30), 1);
            wgmma_commit();
            mbar_wait(s_bar_last + 8 * half, 0);
            wgmma_fence();
#pragma unroll
            for (int ks = 0; ks < 4; ks++)
                wgmma_n64<1>(d, p0 + ks * 4, lo + 512 + ks * 128, (1024u >> 4) | (1u << 30), 1);
            wgmma_commit();
            turn_end();
        };
        float i0, i1;
        auto store_half = [&](int half, const float (&d)[32]) {
#pragma unroll
            for (int i = 0; i < 4; i++) {
                const float* y = d + 8 * i;
                const uint32_t e0 = pack_bf16(y[0] * i0, y[1] * i0), e1 = pack_bf16(y[2] * i1, y[3] * i1);
                const uint32_t f0 = pack_bf16(y[4] * i0, y[5] * i0), f1 = pack_bf16(y[6] * i1, y[7] * i1);
                asm volatile("stmatrix.sync.aligned.m8n8.x4.shared.b16 [%0], {%1, %2, %3, %4};"
                             ::"r"((st_addr ^ (32 * i)) + half * 2048), "r"(e0), "r"(e1), "r"(f0), "r"(f1) : "memory");
            }
            __syncwarp();
#pragma unroll
            for (int i = 0; i < 4; i++) {
                uint4 v;
                asm volatile("ld.shared.v4.b32 {%0, %1, %2, %3}, [%4];" : "=r"(v.x), "=r"(v.y), "=r"(v.z), "=r"(v.w)
                             : "r"((ld_addr ^ (64 * (i & 1))) + i * 512 + half * 2048) : "memory");
                asm volatile("st.global.v4.b32 [%0], {%1, %2, %3, %4};" ::"l"(dst + i * 1024 + half * 128),
                             "r"(v.x), "r"(v.y), "r"(v.z), "r"(v.w) : "memory");
            }
        };
        float oa[32], ob[32];
#pragma unroll
        for (int i = 0; i < 32; i++) {
            asm volatile("mov.b32 %0, %1;" : "=f"(oa[i]) : "f"(o[i]));
            asm volatile("mov.b32 %0, %1;" : "=f"(ob[i]) : "f"(o[32 + i]));
        }
        {
            const uint32_t lo = desc_base + (kSlotBytes >> 4) + rv.slot * (2 * kSlotBytes >> 4);
            mbar_wait(s_bar + 32 * rv.slot + 8, rv.phase);
            turn_begin();
            wgmma_fence();
#pragma unroll
            for (int ks = 0; ks < 4; ks++) wgmma_n64<1>(ob, p + ks * 4, lo + 64 + ks * 256, kDescHi, 1);
#pragma unroll
            for (int ks = 0; ks < 4; ks++) wgmma_n64<1>(oa, p + ks * 4, lo + ks * 256, kDescHi, 1);
            wgmma_commit();
            turn_end();
            rv.advance();
        }
        i0 = l0 + __shfl_xor_sync(~0u, l0, 1);
        i1 = l1 + __shfl_xor_sync(~0u, l1, 1);
        i0 += __shfl_xor_sync(~0u, i0, 2);
        i1 += __shfl_xor_sync(~0u, i1, 2);
        asm("rcp.approx.ftz.f32 %0, %0;" : "+f"(i0));
        asm("rcp.approx.ftz.f32 %0, %0;" : "+f"(i1));
        mbar_arrive_if(s_bar, i0 + i1 < 0.f);
        pv_half(0, rv, oa);
        rv.advance();
        wgmma_wait<0>();
        fence_regs(oa);
        store_half(0, oa);
        fence_regs(ob);
        pv_half(1, rv, ob);
        wgmma_wait<0>();
        fence_regs(ob);
        store_half(1, ob);
    }
}

typedef CUresult (*EncodeTiledFn)(CUtensorMap*, CUtensorMapDataType, cuuint32_t, void*, const cuuint64_t*,
                                  const cuuint64_t*, const cuuint32_t*, const cuuint32_t*, CUtensorMapInterleave,
                                  CUtensorMapSwizzle, CUtensorMapL2promotion, CUtensorMapFloatOOBfill);

}

extern "C" void kernel_launch(void* const* d_in, const int* in_sizes, int n_in, void* d_out, int out_size) {
    (void)n_in; (void)out_size;
    const int num_phys = in_sizes[1] / (kPage * kHkv * kD);

    static EncodeTiledFn encode = nullptr;
    static unsigned* progress = nullptr;
    static float tile_ns = 0.f;
    if (!encode) {
        int dev = 0, khz = 0, bits = 0;
        cudaGetDevice(&dev);
        cudaDeviceGetAttribute(&khz, cudaDevAttrMemoryClockRate, dev);
        cudaDeviceGetAttribute(&bits, cudaDevAttrGlobalMemoryBusWidth, dev);
        const float peak_gbs = 2.f * (float)khz * (float)(bits / 8) * 1e-6f;
        tile_ns = 2 * kSlotBytes / (kDramEfficiency * (peak_gbs > 0.f ? peak_gbs : 3352.f));
        cudaGetSymbolAddress((void**)&progress, g_progress);
        cudaDriverEntryPointQueryResult qr;
        cudaGetDriverEntryPoint("cuTensorMapEncodeTiled", (void**)&encode, cudaEnableDefault, &qr);
        cudaFuncSetAttribute(paged_attn_kernel, cudaFuncAttributeMaxDynamicSharedMemorySize, kSmemBytes);
    }
    Maps tm;
    auto cache_map = [&](CUtensorMap* map, void* cache, cuuint32_t halves, cuuint32_t groups) {
        const cuuint64_t dim[4] = {64, 8, 2 * kHkv, (cuuint64_t)num_phys * 2};
        const cuuint64_t str[3] = {kHkv * kD * 2, 128, 8 * kHkv * kD * 2};
        const cuuint32_t box[4] = {64, 8, halves, groups};
        const cuuint32_t es[4] = {1, 1, 1, 1};
        encode(map, CU_TENSOR_MAP_DATA_TYPE_BFLOAT16, 4, cache, dim, str, box, es, CU_TENSOR_MAP_INTERLEAVE_NONE,
               CU_TENSOR_MAP_SWIZZLE_128B, CU_TENSOR_MAP_L2_PROMOTION_L2_128B, CU_TENSOR_MAP_FLOAT_OOB_FILL_NONE);
    };
    for (int kv = 0; kv < 2; kv++) {
        cache_map(&tm.page[kv], d_in[1 + kv], 2, 2);
        cache_map(&tm.group[kv], d_in[1 + kv], 2, 1);
    }
    cache_map(&tm.vhalf, d_in[2], 1, 2);
    {
        const cuuint64_t dim[2] = {kD, (cuuint64_t)kB * kHkv * kRows};
        const cuuint64_t str[1] = {kD * 2};
        const cuuint32_t box[2] = {64, kRows};
        const cuuint32_t es[2] = {1, 1};
        encode(&tm.q, CU_TENSOR_MAP_DATA_TYPE_BFLOAT16, 2, d_in[0], dim, str, box, es, CU_TENSOR_MAP_INTERLEAVE_NONE,
               CU_TENSOR_MAP_SWIZZLE_128B, CU_TENSOR_MAP_L2_PROMOTION_L2_128B, CU_TENSOR_MAP_FLOAT_OOB_FILL_NONE);
    }
    paged_attn_kernel<<<kB * kHkv, kThreads, kSmemBytes>>>(
        (const int*)d_in[4], (const int*)d_in[3], (const __nv_bfloat16*)d_in[0], (__nv_bfloat16*)d_out, progress,
        num_phys * 2, tile_ns, tm);
}
```

```cpp
#include <cuda_runtime.h>
#include <cuda.h>
#include <cuda_bf16.h>
#include <stdint.h>

namespace {

constexpr int kB = 16, kHkv = 8, kD = 128, kPage = 16, kNBPS = 256;
constexpr int kRows = 128;
constexpr int kSkv = kNBPS * kPage;
constexpr int kTileN = 64;
constexpr int kSlotBytes = 16384;
constexpr int kStages = 6;
constexpr float kDramEfficiency = 0.972f;
constexpr float kWindow = 1800.f;
constexpr float kTaper = 980.f;
constexpr float kTaperSpan = 9300.f;
constexpr float kAheadK = 60.f, kAheadV3 = 170.f, kAheadV2 = 135.f;
constexpr float kAheadL1 = 108.f, kAheadL0 = 20.f, kAheadR2 = 100.f, kAheadR1 = 100.f, kAheadR0 = 35.f;
constexpr float kTightL0 = 0.32f, kTightR0 = 0.1f;
constexpr float kStartLag = 600.f;
constexpr float kClockGain = 0.25f;
constexpr float kClockStep = 800.f;
constexpr unsigned kClockWarmup = 200;
constexpr int kLead = 4;
constexpr int kSplit = 2;
constexpr int kEvenTiles = 5;
constexpr int kQPrefetch = 16384;
constexpr float kMaxGrowth = 4096.f;
constexpr int kThreads = 384;

constexpr int kSmemRing = kStages * 2 * kSlotBytes;
constexpr int kSortWords = 160;
constexpr int kSmemHead = 4096;
constexpr int kSmemBytes = 1024 + kSmemHead + kSmemRing;

__device__ __forceinline__ uint32_t smem_u32(const void* p) {
    return (uint32_t)__cvta_generic_to_shared(p);
}
__device__ __forceinline__ void mbar_init(uint32_t bar, uint32_t cnt) {
    asm volatile("mbarrier.init.shared::cta.b64 [%0], %1;" ::"r"(bar), "r"(cnt) : "memory");
}
__device__ __forceinline__ void mbar_expect_tx(uint32_t bar, uint32_t bytes) {
    asm volatile("mbarrier.arrive.expect_tx.shared::cta.b64 _, [%0], %1;" ::"r"(bar), "r"(bytes) : "memory");
}
__device__ __forceinline__ void mbar_arrive_if(uint32_t bar, bool pred) {
    asm volatile("{\n.reg .pred p;\nsetp.ne.u32 p, %1, 0;\n@p mbarrier.arrive.shared::cta.b64 _, [%0];\n}"
                 ::"r"(bar), "r"((uint32_t)pred) : "memory");
}
__device__ __forceinline__ void mbar_wait(uint32_t bar, uint32_t parity) {
    asm volatile(
        "{\n.reg .pred p;\n"
        "WAIT_LOOP:\n"
        "mbarrier.try_wait.parity.shared::cta.b64 p, [%0], %1;\n"
        "@p bra WAIT_DONE;\n"
        "bra WAIT_LOOP;\n"
        "WAIT_DONE:\n}" ::"r"(bar), "r"(parity) : "memory");
}
__device__ __forceinline__ void tma_page(uint32_t dst, const CUtensorMap* tm, uint32_t bar, int c2, int c3, uint64_t pol) {
    asm volatile(
        "cp.async.bulk.tensor.4d.shared::cluster.global.mbarrier::complete_tx::bytes.L2::cache_hint"
        " [%0], [%1, {%3, %3, %4, %5}], [%2], %6;"
        ::"r"(dst), "l"(tm), "r"(bar), "r"(0), "r"(c2), "r"(c3), "l"(pol) : "memory");
}
__device__ __forceinline__ void tma_group(uint32_t dst, const CUtensorMap* tm, uint32_t bar, int c1, int c2, int c3, uint64_t pol) {
    asm volatile(
        "cp.async.bulk.tensor.4d.shared::cluster.global.mbarrier::complete_tx::bytes.L2::cache_hint"
        " [%0], [%1, {%3, %4, %5, %6}], [%2], %7;"
        ::"r"(dst), "l"(tm), "r"(bar), "r"(0), "r"(c1), "r"(c2), "r"(c3), "l"(pol) : "memory");
}
__device__ __forceinline__ void tma_2d(uint32_t dst, const CUtensorMap* tm, uint32_t bar, int c0, int c1) {
    asm volatile(
        "cp.async.bulk.tensor.2d.shared::cluster.global.mbarrier::complete_tx::bytes"
        " [%0], [%1, {%3, %4}], [%2];" ::"r"(dst), "l"(tm), "r"(bar), "r"(c0), "r"(c1)
        : "memory");
}
__device__ __forceinline__ int4 ldg_v4(const int4* p) {
    int4 v;
    asm volatile("ld.global.nc.v4.b32 {%0, %1, %2, %3}, [%4];" : "=r"(v.x), "=r"(v.y), "=r"(v.z), "=r"(v.w) : "l"(p) : "memory");
    return v;
}
__device__ __forceinline__ bool elect_one() {
    uint32_t pred;
    asm volatile("{\n.reg .pred p;\nelect.sync _|p, 0xffffffff;\nselp.u32 %0, 1, 0, p;\n}" : "=r"(pred));
    return pred;
}
__device__ __forceinline__ void wg1_sync(int id, int wg) {
    asm volatile("{\n.reg .pred p;\nsetp.ne.u32 p, %1, 0;\n@p bar.sync %0, 256;\n}" ::"r"(id), "r"(wg) : "memory");
}
__device__ __forceinline__ void wg0_arrive(int id, int wg) {
    asm volatile("{\n.reg .pred p;\nsetp.eq.u32 p, %1, 0;\n@p bar.arrive %0, 256;\n}" ::"r"(id), "r"(wg) : "memory");
}
__device__ __forceinline__ void wgmma_fence() { asm volatile("wgmma.fence.sync.aligned;" ::: "memory"); }
__device__ __forceinline__ void wgmma_commit() { asm volatile("wgmma.commit_group.sync.aligned;" ::: "memory"); }
template <int N>
__device__ __forceinline__ void wgmma_wait() { asm volatile("wgmma.wait_group.sync.aligned %0;" ::"n"(N) : "memory"); }
template <int N>
__device__ __forceinline__ void fence_regs(float (&r)[N]) {
#pragma unroll
    for (int i = 0; i < N; i++) asm volatile("" : "+f"(r[i])::"memory");
}
template <int N>
__device__ __forceinline__ void fence_regs(uint32_t (&r)[N]) {
#pragma unroll
    for (int i = 0; i < N; i++) asm volatile("" : "+r"(r[i])::"memory");
}
__device__ __forceinline__ float ex2(float x) {
    float y;
    asm("ex2.approx.ftz.f32 %0, %1;" : "=f"(y) : "f"(x));
    return y;
}
__device__ __forceinline__ uint32_t pack_bf16(float lo, float hi) {
    uint32_t r;
    asm("cvt.rn.bf16x2.f32 %0, %1, %2;" : "=r"(r) : "f"(hi), "f"(lo));
    return r;
}

__device__ __forceinline__ void scale_bf16(uint32_t& p, float a) {
    p = pack_bf16(__uint_as_float(p << 16) * a, __uint_as_float(p & 0xffff0000u) * a);
}

template <int TB>
__device__ __forceinline__ void wgmma_n64(float (&d)[32], const uint32_t* a, uint32_t desc_lo, uint32_t desc_hi, int scale_d) {
    asm volatile(
        "{\n.reg .pred p;\n.reg .b64 db;\n"
        "setp.ne.b32 p, %38, 0;\n"
        "mov.b64 db, {%36, %37};\n"
        "wgmma.mma_async.sync.aligned.m64n64k16.f32.bf16.bf16 "
        "{%0, %1, %2, %3, %4, %5, %6, %7, %8, %9, %10, %11, %12, %13, %14, %15, "
        "%16, %17, %18, %19, %20, %21, %22, %23, %24, %25, %26, %27, %28, %29, %30, %31}, "
        "{%32, %33, %34, %35}, db, p, 1, 1, %39;\n}"
        : "+f"(d[0]), "+f"(d[1]), "+f"(d[2]), "+f"(d[3]), "+f"(d[4]), "+f"(d[5]), "+f"(d[6]), "+f"(d[7]),
          "+f"(d[8]), "+f"(d[9]), "+f"(d[10]), "+f"(d[11]), "+f"(d[12]), "+f"(d[13]), "+f"(d[14]), "+f"(d[15]),
          "+f"(d[16]), "+f"(d[17]), "+f"(d[18]), "+f"(d[19]), "+f"(d[20]), "+f"(d[21]), "+f"(d[22]), "+f"(d[23]),
          "+f"(d[24]), "+f"(d[25]), "+f"(d[26]), "+f"(d[27]), "+f"(d[28]), "+f"(d[29]), "+f"(d[30]), "+f"(d[31])
        : "r"(a[0]), "r"(a[1]), "r"(a[2]), "r"(a[3]), "r"(desc_lo), "r"(desc_hi), "r"(scale_d), "n"(TB));
}
__device__ __forceinline__ void wgmma_pv(float (&d)[64], const uint32_t* a, uint32_t desc_lo, uint32_t desc_hi, int scale_d) {
    asm volatile(
        "{\n.reg .pred p;\n.reg .b64 db;\n"
        "setp.ne.b32 p, %70, 0;\n"
        "mov.b64 db, {%68, %69};\n"
        "wgmma.mma_async.sync.aligned.m64n128k16.f32.bf16.bf16 "
        "{%0, %1, %2, %3, %4, %5, %6, %7, %8, %9, %10, %11, %12, %13, %14, %15, "
        "%16, %17, %18, %19, %20, %21, %22, %23, %24, %25, %26, %27, %28, %29, %30, %31, "
        "%32, %33, %34, %35, %36, %37, %38, %39, %40, %41, %42, %43, %44, %45, %46, %47, "
        "%48, %49, %50, %51, %52, %53, %54, %55, %56, %57, %58, %59, %60, %61, %62, %63}, "
        "{%64, %65, %66, %67}, db, p, 1, 1, 1;\n}"
        : "+f"(d[0]), "+f"(d[1]), "+f"(d[2]), "+f"(d[3]), "+f"(d[4]), "+f"(d[5]), "+f"(d[6]), "+f"(d[7]),
          "+f"(d[8]), "+f"(d[9]), "+f"(d[10]), "+f"(d[11]), "+f"(d[12]), "+f"(d[13]), "+f"(d[14]), "+f"(d[15]),
          "+f"(d[16]), "+f"(d[17]), "+f"(d[18]), "+f"(d[19]), "+f"(d[20]), "+f"(d[21]), "+f"(d[22]), "+f"(d[23]),
          "+f"(d[24]), "+f"(d[25]), "+f"(d[26]), "+f"(d[27]), "+f"(d[28]), "+f"(d[29]), "+f"(d[30]), "+f"(d[31]),
          "+f"(d[32]), "+f"(d[33]), "+f"(d[34]), "+f"(d[35]), "+f"(d[36]), "+f"(d[37]), "+f"(d[38]), "+f"(d[39]),
          "+f"(d[40]), "+f"(d[41]), "+f"(d[42]), "+f"(d[43]), "+f"(d[44]), "+f"(d[45]), "+f"(d[46]), "+f"(d[47]),
          "+f"(d[48]), "+f"(d[49]), "+f"(d[50]), "+f"(d[51]), "+f"(d[52]), "+f"(d[53]), "+f"(d[54]), "+f"(d[55]),
          "+f"(d[56]), "+f"(d[57]), "+f"(d[58]), "+f"(d[59]), "+f"(d[60]), "+f"(d[61]), "+f"(d[62]), "+f"(d[63])
        : "r"(a[0]), "r"(a[1]), "r"(a[2]), "r"(a[3]), "r"(desc_lo), "r"(desc_hi), "r"(scale_d));
}

__device__ __forceinline__ int bcast(int v, int lane, int src) {
    return __reduce_max_sync(~0u, lane == src ? v : 0);
}

__device__ __forceinline__ void sort_pages(const int4& row0, const int4& row1, int first, int n, int lane,
                                           uint32_t s_list, uint32_t s_bits) {
    constexpr int kW = kSortWords / 32;
    const uint32_t e[8] = {(uint32_t)row0.x, (uint32_t)row0.y, (uint32_t)row0.z, (uint32_t)row0.w,
                           (uint32_t)row1.x, (uint32_t)row1.y, (uint32_t)row1.z, (uint32_t)row1.w};
    uint32_t wa[8];
#pragma unroll
    for (int i = 0; i < 8; i++) {
        const bool use = (unsigned)(lane - first + (i >> 2) * 32) < (unsigned)n && e[i] < kSortWords * 32;
        wa[i] = s_bits + (use ? e[i] >> 5 : 0) * 8;
        asm volatile("{\n.reg .pred p;\nsetp.ne.u32 p, %2, 0;\n@p red.shared.or.b32 [%0], %1;\n}"
                     ::"r"(wa[i]), "r"(1u << (e[i] & 31)), "r"((uint32_t)use) : "memory");
    }
    __syncwarp();
    uint32_t cnt[kW + 1];
    cnt[0] = 0;
#pragma unroll
    for (int i = 0; i < kW; i++) {
        uint32_t w;
        asm volatile("ld.shared.b32 %0, [%1];" : "=r"(w) : "r"(s_bits + (lane * kW + i) * 8) : "memory");
        cnt[i + 1] = cnt[i] + __popc(w);
    }
    uint32_t scan = cnt[kW];
#pragma unroll
    for (int o = 1; o < 32; o <<= 1) {
        const uint32_t v = __shfl_up_sync(~0u, scan, o);
        if (lane >= o) scan += v;
    }
    const bool sorted = __shfl_sync(~0u, scan, 31) == (uint32_t)n * 4;
#pragma unroll
    for (int i = 0; i < kW; i++)
        asm volatile("st.shared.b32 [%0], %1;" ::"r"(s_bits + (lane * kW + i) * 8 + 4), "r"(scan - cnt[kW] + cnt[i]) : "memory");
    __syncwarp();
#pragma unroll
    for (int i = 0; i < 8; i++) {
        uint32_t w, base;
        asm volatile("ld.shared.v2.b32 {%0, %1}, [%2];" : "=r"(w), "=r"(base) : "r"(wa[i]) : "memory");
        wa[i] = base + __popc(w & ((1u << (e[i] & 31)) - 1));
    }
#pragma unroll
    for (int i = 0; i < 8; i++) {
        const uint32_t pos = sorted ? wa[i] : (lane - first) * 4 + (i >> 2) * 128 + (i & 3);
        asm volatile("{\n.reg .pred p;\nsetp.ne.u32 p, %2, 0;\n@p st.shared.b32 [%0], %1;\n}"
                     ::"r"(s_list + pos * 4), "r"(e[i] * 2), "r"((uint32_t)((unsigned)(lane - first + (i >> 2) * 32) < (unsigned)n)) : "memory");
    }
}

__device__ unsigned g_progress;

struct Maps {
    CUtensorMap page[2];
    CUtensorMap group[2];
    CUtensorMap vhalf;
    CUtensorMap q;
    CUtensorMap out;
};

struct Ring {
    int slot;
    uint32_t phase;
    __device__ __forceinline__ void advance() {
        if (++slot == kStages) { slot = 0; phase ^= 1; }
    }
};

__global__ void __launch_bounds__(kThreads, 1)
paged_attn_kernel(const int* __restrict__ ctx, const int* __restrict__ table, const __nv_bfloat16* __restrict__ q,
                  __nv_bfloat16* __restrict__ out, unsigned* progress, int oob_coord, float tile_ns,
                  const __grid_constant__ Maps tm) {
    extern __shared__ uint8_t smem_raw[];
    const int tid = threadIdx.x, lane = tid & 31;
    const int b = blockIdx.x / kHkv, h = blockIdx.x % kHkv;
    const int bh = b * kHkv + h;
    const __nv_bfloat16* q_tile = q + (size_t)bh * kRows * kD;
    if (elect_one()) asm volatile("cp.async.bulk.prefetch.L2.global [%0], %1;" ::"l"(q_tile), "r"(16) : "memory");
    if (tid == 0) asm volatile("cp.async.bulk.prefetch.L2.global [%0], %1;" ::"l"(q_tile), "r"(kQPrefetch) : "memory");
    uint32_t t_begin;
    asm volatile("mov.u32 %0, %globaltimer_lo;" : "=r"(t_begin) :: "memory");
    int cl;
    int4 row0, row1;
    if (tid >= 256) {
        const bool head = tid >> 5 == 10;
        const int4* row = reinterpret_cast<const int4*>(table + b * kNBPS) + (head ? 0 : lane);
        row0 = ldg_v4(row);
        asm volatile("ld.global.nc.b32 %0, [%1];" : "=r"(cl) : "l"(ctx + (lane & (kB - 1))) : "memory");
        row1 = ldg_v4(row + (head ? 0 : 32));
    }
    const int warp = __shfl_sync(~0u, tid >> 5, 0);
    const uint32_t sbase = __reduce_max_sync(~0u, (smem_u32(smem_raw) + 1023 + kSmemHead) & ~1023u);
    const uint32_t s_bits = sbase - 4096, s_list = sbase - 2048;
    const uint32_t s_bar = sbase - 1024, s_clock = sbase - 512;
    const uint32_t s_bar_last = s_bar + 32 * kStages;
    static_assert(kStages == 6 && kSplit <= 4, "barrier layout");

    if (warp < 8) {
        if (elect_one()) {
            mbar_init(s_bar + 32 * warp, 1);
            mbar_init(s_bar + 32 * warp + 8, 1);
            mbar_init(s_bar + 32 * warp + 16, warp < kStages ? 9 : 1);
            mbar_init(s_bar + 32 * warp + 24, warp < kStages ? 8 : 1);
            asm volatile("fence.mbarrier_init.release.cluster;" ::: "memory");
            if (warp < 2 || warp >= kStages) {
                mbar_expect_tx(s_bar + 32 * warp, warp < 2 ? kSlotBytes : kSlotBytes / 2);
                mbar_expect_tx(s_bar + 32 * warp + 8, warp < 2 ? kSlotBytes : kSlotBytes / 2);
            }
            if (warp >= kStages) {
                mbar_expect_tx(s_bar + 32 * warp + 16, kSlotBytes / 2);
                mbar_expect_tx(s_bar + 32 * warp + 24, kSlotBytes / 2);
            }
            if (warp == 0) {
                asm volatile("fence.proxy.async.shared::cta;" ::: "memory");
                tma_2d(sbase, &tm.q, s_bar, 0, bh * kRows);
                tma_2d(sbase + kSlotBytes, &tm.q, s_bar + 8, 64, bh * kRows);
            }
        }
    } else if (warp == 8) {
#pragma unroll
        for (int i = 0; i < kSortWords / 32; i++)
            asm volatile("st.shared.b32 [%0], %1;" ::"r"(s_bits + (lane * (kSortWords / 32) + i) * 8), "r"(0) : "memory");
    }
    __syncthreads();

    if (warp >= 8) {
        asm volatile("setmaxnreg.dec.sync.aligned.u32 40;");
        const int kv = (warp >> 1) & 1;
        uint64_t pol;
        asm volatile("createpolicy.fractional.L2::evict_first.b64 %0, 1.0;" : "=l"(pol));
        const int len_l = cl <= 0 ? kSkv : min(cl, kSkv);
        const int len = bcast(len_l, lane, b);
        const int top = (len - 1) / kTileN;
        const int n = max(top, kLead - 1);
        const int early = top > kLead;
        if (warp == 10 && early && elect_one()) {
#pragma unroll
            for (int i = 0; i < 2; i++) {
                const uint32_t dst = sbase + (4 + i) * kSlotBytes, bar = s_bar + 64 + 8 * i;
                mbar_expect_tx(bar, kSlotBytes);
                tma_page(dst, &tm.page[i], bar, h * 2, row0.x * 2, pol);
                tma_page(dst + 4096, &tm.page[i], bar, h * 2, row0.y * 2, pol);
                tma_page(dst + 8192, &tm.page[i], bar, h * 2, row0.z * 2, pol);
                tma_page(dst + 12288, &tm.page[i], bar, h * 2, row0.w * 2, pol);
            }
        }
        if (warp & 1) {
            const int4 src = top < 32 ? row0 : row1;
            const int p0 = bcast(src.x, lane, top & 31) * 2, p1 = bcast(src.y, lane, top & 31) * 2;
            const int p2 = bcast(src.z, lane, top & 31) * 2, p3 = bcast(src.w, lane, top & 31) * 2;
            const int rem = len - top * kTileN, full = (rem - 1) / kPage, r = rem - full * kPage;
            const int last = full == 0 ? p0 : full == 1 ? p1 : full == 2 ? p2 : p3;
            const uint32_t off = (3 - full) * 4096;
            if (elect_one()) {
                const uint32_t dst = sbase + (2 + kv) * kSlotBytes, bar = s_bar + 32 + 8 * kv;
                tma_page(dst + ((off + 4096) & 0x3fff), &tm.page[kv], bar, h * 2, full > 0 ? p0 : oob_coord, pol);
                tma_page(dst + ((off + 8192) & 0x3fff), &tm.page[kv], bar, h * 2, full > 1 ? p1 : oob_coord, pol);
                tma_page(dst + ((off + 12288) & 0x3fff), &tm.page[kv], bar, h * 2, full > 2 ? p2 : oob_coord, pol);
                tma_group(dst + off, &tm.group[kv], bar, r - 16, h * 2, last + 1, pol);
                tma_group(dst + off + 2048, &tm.group[kv], bar, min(r - 8, 0), h * 2, last, pol);
                asm volatile("prefetch.tensormap [%0];" ::"l"(kv ? &tm.vhalf : &tm.out) : "memory");
            }
            {
                asm volatile("bar.sync %0, 160;" ::"r"(2 + kv) : "memory");
                asm volatile("fence.proxy.async.shared::cta;" ::: "memory");
                if (elect_one()) {
                    asm volatile("cp.async.bulk.tensor.2d.global.shared::cta.bulk_group [%0, {%1, %2}], [%3];"
                                 ::"l"(&tm.out), "r"(0), "r"(bh * kRows + kv * 64),
                                 "r"(sbase + ((n + 3) % kStages * 2 + kv) * kSlotBytes) : "memory");
                    asm volatile("cp.async.bulk.commit_group;" ::: "memory");
                }
            }
            asm volatile("cp.async.bulk.wait_group.read 0;" ::: "memory");
            return;
        }
        const int full_l = lane < kB ? (len_l - 1) / kTileN : 0;
        const float t_all = (float)(__reduce_add_sync(~0u, full_l) * kHkv) * tile_ns;
        float origin = (kB * kHkv + __reduce_add_sync(~0u, lane < kB ? len_l - full_l * kTileN : 0) * (1.f / 8)) * tile_ns + kStartLag;
        if (warp == 10) {
            if (lane == 0) {
                const float gain = fminf(__fdividef(kClockGain * t_all, (float)(n * kB * kHkv) * tile_ns), 0.5f);
                mbar_arrive_if(s_bar + 16, true);
                mbar_arrive_if(s_bar + 48, true);
                Ring m{2, 0};
                unsigned g;
#pragma unroll 1
                for (int t = n - 1; t >= kLead - 2; t--) {
                    if (t == kLead - 2) m.advance();
                    mbar_wait(s_bar + 32 * m.slot, m.phase);
                    mbar_arrive_if(s_bar + 32 * m.slot + 16, true);
                    m.advance();
                    uint32_t now;
                    asm volatile("mov.u32 %0, %globaltimer_lo;" : "=r"(now) :: "memory");
                    asm volatile("atom.relaxed.gpu.global.add.u32 %0, [%1], 1;" : "=r"(g) : "l"(progress) : "memory");
                    g &= 0xfffff;
                    const float d = (float)(int)(now - t_begin) - (float)g * tile_ns - origin;
                    if (g >= kClockWarmup) origin = fmaf(fminf(d, kClockStep), gain, origin);
                    asm volatile("st.volatile.shared.b32 [%0], %1;" ::"r"(s_clock), "r"(t_begin + (int)origin) : "memory");
                }
                asm volatile("atom.relaxed.gpu.global.add.u32 %0, [%1], 0x100000;" : "=r"(g) : "l"(progress) : "memory");
                if ((g >> 20) == kB * kHkv - 1) asm volatile("st.relaxed.gpu.global.u32 [%0], 0;" ::"l"(progress) : "memory");
            }
            return;
        }
        asm volatile("st.volatile.shared.b32 [%0], %1;" ::"r"(s_clock), "r"(t_begin + (int)origin) : "memory");
        if (lane < 4 * (kLead - 1)) asm volatile("st.shared.b32 [%0], %1;" ::"r"(s_list + lane * 4), "r"(oob_coord) : "memory");
        sort_pages(row0, row1, early, top - early, lane, s_list, s_bits);
        __syncwarp();
        auto pages = [&](int t) {
            int4 pg;
            asm volatile("ld.shared.v4.b32 {%0, %1, %2, %3}, [%4];" : "=r"(pg.x), "=r"(pg.y), "=r"(pg.z), "=r"(pg.w)
                         : "r"(s_list + t * 16) : "memory");
            return pg;
        };
        const float dt_end = tile_ns * (kB * kHkv / 2);
        const float stagger = dt_end * ((b * 7 % kB) + 0.5f) * (1.f / kB);
        const float dt = __fdividef(t_all - dt_end * (2 * kEvenTiles), (float)(2 * max(n - kEvenTiles, 1)));
        float left = (n > kEvenTiles ? t_all : dt_end * (float)(2 * n)) - stagger;
        auto wait_due = [&](float step, float ahead = 0.f) {
            const int due = (int)(t_all - kWindow - left + fmaxf(fmaf(left, -kTaper / kTaperSpan, kTaper), 0.f) - ahead);
            left -= step;
#pragma unroll 1
            while (true) {
                uint32_t now, org;
                asm volatile("ld.volatile.shared.b32 %0, [%1];" : "=r"(org) : "r"(s_clock) : "memory");
                asm volatile("mov.u32 %0, %globaltimer_lo;" : "=r"(now));
                const int wait = due - (int)(now - org);
                if (wait <= 0) break;
                if (wait > 64) __nanosleep(min(wait >> 1, 200));
            }
        };
        auto acquire = [&](const Ring& r, int kv, float step, float ahead = 0.f) {
            const uint32_t bar = s_bar + 32 * r.slot + 8 * kv;
            mbar_wait(bar + 16, r.phase ^ 1);
            if (lane == 0) mbar_expect_tx(bar, kSlotBytes);
            wait_due(step, ahead);
            return bar;
        };
        auto load4 = [&](uint32_t dst, uint32_t stride, const CUtensorMap* map, uint32_t bar, int c2, const int4& pg) {
            if (elect_one()) {
                tma_page(dst, map, bar, c2, pg.x, pol);
                tma_page(dst + stride, map, bar, c2, pg.y, pol);
                tma_page(dst + 2 * stride, map, bar, c2, pg.z, pol);
                tma_page(dst + 3 * stride, map, bar, c2, pg.w, pol);
            }
        };
        Ring r{2 + early, 0};
        if (early) left -= 2.f * (n > kEvenTiles ? dt : dt_end);
#pragma unroll 1
        for (int t = n - 1 - early; t >= kLead; t--) {
            const int4 pg = pages(t);
            const uint32_t dst = sbase + 2 * r.slot * kSlotBytes;
            const float step = t < kEvenTiles ? dt_end : dt;
            load4(dst, 4096, &tm.page[0], acquire(r, 0, step), h * 2, pg);
            load4(dst + kSlotBytes, 4096, &tm.page[1], acquire(r, 1, step), h * 2, pg);
            r.advance();
        }
        Ring rv = r;
#pragma unroll 1
        for (int i = 0; i < 2 * kLead - kSplit; i++) {
            const int kv = i >= kLead;
            const int t = (kv ? 2 * kLead : kLead) - 1 - i;
            if (t >= n) continue;
            const int4 pg = pages(t);
            const Ring cur = kv ? rv : r;
            load4(sbase + (2 * cur.slot + kv) * kSlotBytes, 4096, &tm.page[kv],
                  acquire(cur, kv, dt_end, kv ? t == 3 ? kAheadV3 : kAheadV2 : i ? kAheadK : 0.f), h * 2, pg);
            if (kv) rv.advance(); else r.advance();
        }
        left += 0.5f * stagger;
#pragma unroll 1
        for (int j = 0; j < 2 * kSplit; j++) {
            const int half = j >= kSplit, t = (half ? 2 * kSplit : kSplit) - 1 - j;
            const int4 pg = pages(t);
            mbar_wait(s_bar + 32 * rv.slot + 24, rv.phase ^ 1);
            wait_due(0.5f * dt_end, t > 1 ? half ? kAheadR2 : kAheadV2 : t ? half ? kAheadR1 : kAheadL1
                                          : half ? fmaf(stagger, kTightR0, kAheadR0) : fmaf(stagger, kTightL0, kAheadL0));
            load4(sbase + (2 * rv.slot + 1) * kSlotBytes + (j & 1) * 8192, 2048, &tm.vhalf, s_bar_last + 8 * j, h * 2 + half, pg);
            if (j & 1) rv.advance();
        }
    } else {
        asm volatile("setmaxnreg.inc.sync.aligned.u32 232;");
        const int wg = warp >> 2;
        const int clb = __reduce_max_sync(~0u, __ldg(ctx + b));
        const int len = clb <= 0 ? kSkv : min(clb, kSkv);
        const int top = (len - 1) / kTileN;
        const float c = clb <= 0 ? 0.f : 0.08838834764831845f * 1.4426950408889634f;

        if (wg == 1) asm volatile("bar.arrive 4, 256;" ::: "memory");
        constexpr uint32_t kDescHi = (2048u >> 4) | (1u << 30);
        constexpr uint32_t kLboK = 1u << 16, kLboV = (1024u >> 4) << 16;
        const uint32_t desc_base = (sbase & 0x3FFFF) >> 4;

        const uint32_t stg = sbase + (max(top, kLead - 1) + 3) % kStages * 2 * kSlotBytes + wg * kSlotBytes + (warp & 3) * 2048;
        const uint32_t st_addr = __shfl_sync(~0u, stg + (lane & 7) * 128 + (((lane >> 3) ^ (lane & 7)) << 4), lane);
        const uint32_t ld_addr = __shfl_sync(~0u, stg + (lane >> 3) * 128 + (((lane & 7) ^ (lane >> 3)) << 4), lane);
        const uint32_t out_off = __shfl_sync(~0u, ((bh * kRows + warp * 16 + (lane >> 3)) * kD + (lane & 7) * 8) * 2, lane);
        float o[64], s[32];
        uint32_t qf[32], p[16];
#pragma unroll
        for (int i = 0; i < 16; i++) p[i] = 0;
#pragma unroll
        for (int i = 0; i < 64; i++) o[i] = 0.f;
#pragma unroll
        for (int i = 0; i < 32; i++) asm volatile("" : "=f"(s[i]));
        float m0 = -1e30f, m1 = -1e30f, n0 = -m0 * c, n1 = n0, l0 = 0.f, l1 = 0.f;
        {
            const int row = wg * 64 + (warp & 3) * 16 + (lane & 7) + ((lane >> 3) & 1) * 8;
#pragma unroll
            for (int half = 0; half < 2; half++) {
                mbar_wait(s_bar + 8 * half, 0);
                const uint32_t base = sbase + half * kSlotBytes + row * 128;
#pragma unroll
                for (int ks = 0; ks < 4; ks++) {
                    const uint32_t addr = base + (((ks * 2 + (lane >> 4)) ^ (lane & 7)) << 4);
                    uint32_t* f = qf + (half * 4 + ks) * 4;
                    asm volatile("ldmatrix.sync.aligned.m8n8.x4.shared.b16 {%0, %1, %2, %3}, [%4];"
                                 : "=r"(f[0]), "=r"(f[1]), "=r"(f[2]), "=r"(f[3]) : "r"(addr) : "memory");
                }
            }
            __syncwarp();
            mbar_arrive_if(s_bar + 16, lane == 0);
        }

        float w0, w1;
        auto exps = [&](uint32_t (&p)[16]) {
            float v0, v1;
#pragma unroll
            for (int i = 0; i < 8; i++) {
                const float e0 = ex2(fmaf(s[4 * i], c, n0)), e1 = ex2(fmaf(s[4 * i + 1], c, n0));
                const float e2 = ex2(fmaf(s[4 * i + 2], c, n1)), e3 = ex2(fmaf(s[4 * i + 3], c, n1));
                w0 = i ? w0 + e0 : e0;
                v0 = i ? v0 + e1 : e1;
                w1 = i ? w1 + e2 : e2;
                v1 = i ? v1 + e3 : e3;
                p[2 * i] = pack_bf16(e0, e1);
                p[2 * i + 1] = pack_bf16(e2, e3);
            }
            w0 += v0;
            w1 += v1;
        };
        auto must_redo = [&](int skip) { return __any_sync(~0u, fmaxf(w0, w1) > kMaxGrowth || skip > 0); };
        auto redo = [&](int skip, uint32_t (&p)[16], auto&& rescale_pending) {
            const int col = (lane & 3) * 2;
            float x0 = m0, x1 = m1;
#pragma unroll
            for (int i = 0; i < 8; i++) {
                if (i * 8 + col < skip) { s[4 * i] = -INFINITY; s[4 * i + 2] = -INFINITY; }
                if (i * 8 + col + 1 < skip) { s[4 * i + 1] = -INFINITY; s[4 * i + 3] = -INFINITY; }
                x0 = fmaxf(x0, fmaxf(s[4 * i], s[4 * i + 1]));
                x1 = fmaxf(x1, fmaxf(s[4 * i + 2], s[4 * i + 3]));
            }
            x0 = fmaxf(x0, __shfl_xor_sync(~0u, x0, 1));
            x1 = fmaxf(x1, __shfl_xor_sync(~0u, x1, 1));
            x0 = fmaxf(x0, __shfl_xor_sync(~0u, x0, 2));
            x1 = fmaxf(x1, __shfl_xor_sync(~0u, x1, 2));
            const float a0 = ex2((m0 - x0) * c), a1 = ex2((m1 - x1) * c);
            m0 = x0;
            m1 = x1;
            n0 = -x0 * c;
            n1 = -x1 * c;
            l0 *= a0;
            l1 *= a1;
#pragma unroll
            for (int i = 0; i < 16; i++) {
                o[4 * i] *= a0;
                o[4 * i + 1] *= a0;
                o[4 * i + 2] *= a1;
                o[4 * i + 3] *= a1;
                rescale_pending(i, i & 1 ? a1 : a0);
            }
            exps(p);
        };
        auto issue_qk = [&](int slot) {
            const uint32_t lo = desc_base + kLboK + slot * (2 * kSlotBytes >> 4);
#pragma unroll
            for (int ks = 0; ks < 8; ks++)
                wgmma_n64<0>(s, qf + ks * 4, lo + (ks >> 2) * 64 + (ks & 3) * 2, kDescHi, ks != 0);
        };
        auto issue_pv = [&](int slot) {
            const uint32_t lo = desc_base + kLboV + (kSlotBytes >> 4) + slot * (2 * kSlotBytes >> 4);
#pragma unroll
            for (int ks = 0; ks < 4; ks++) wgmma_pv(o, p + ks * 4, lo + ks * 256, kDescHi, 1);
        };
        auto turn_begin = [&]() {
            asm volatile("bar.sync %0, 256;" ::"r"(4 + wg) : "memory");
        };
        auto turn_end = [&]() {
            asm volatile("bar.arrive %0, 256;" ::"r"(5 - wg) : "memory");
        };

        Ring rv{0, 0}, r{1, 0};
        int skip = (top + 1) * kTileN - len;
        int t = max(top, kLead - 1);
        fence_regs(qf);
#pragma unroll 1
        do {
            const uint32_t bar_v = s_bar + 32 * rv.slot + 8, bar_k = s_bar + 32 * r.slot;
            fence_regs(s);
            fence_regs(o);
            fence_regs(p);
            mbar_wait(bar_v, rv.phase);
            turn_begin();
            wgmma_fence();
            issue_pv(rv.slot);
            wgmma_commit();
            mbar_wait(bar_k, r.phase);
            wgmma_fence();
            issue_qk(r.slot);
            wgmma_commit();
            turn_end();
            rv = r;
            r.advance();
            wgmma_wait<0>();
            fence_regs(s);
            fence_regs(o);
            fence_regs(p);
            mbar_arrive_if(bar_k + 16, lane == 0);
            mbar_arrive_if(bar_v + 16, lane == 1);
            exps(p);
            if (must_redo(skip)) redo(skip, p, [](int, float) {});
            skip = 0;
            l0 += w0;
            l1 += w1;
        } while (--t >= kLead - 1);
        auto scores = [&](int t, uint32_t (&e)[16], auto&& rescale_pending) {
            fence_regs(s);
            turn_begin();
            mbar_wait(s_bar + 32 * r.slot, r.phase);
            wgmma_fence();
            issue_qk(r.slot);
            wgmma_commit();
            turn_end();
            r.advance();
            wgmma_wait<0>();
            fence_regs(s);
            exps(e);
            if (must_redo(top <= t)) redo(top <= t ? kTileN : 0, e, rescale_pending);
            l0 += w0;
            l1 += w1;
        };
        uint32_t p2[16], p1[16], p0[16];
        scores(2, p2, [&](int i, float a) { scale_bf16(p[i], a); });
        scores(1, p1, [&](int i, float a) { scale_bf16(p[i], a); scale_bf16(p2[i], a); });
        scores(0, p0, [&](int i, float a) { scale_bf16(p[i], a); scale_bf16(p2[i], a); scale_bf16(p1[i], a); });
        fence_regs(o);
        fence_regs(p);
        fence_regs(p2);
        fence_regs(p1);
        fence_regs(p0);
        float oa[32], ob[32];
#pragma unroll
        for (int i = 0; i < 32; i++) {
            asm volatile("mov.b32 %0, %1;" : "=f"(oa[i]) : "f"(o[i]));
            asm volatile("mov.b32 %0, %1;" : "=f"(ob[i]) : "f"(o[32 + i]));
        }
        auto pv_tile = [&](const uint32_t (&p)[16]) {
            const uint32_t lo = desc_base + (kSlotBytes >> 4) + rv.slot * (2 * kSlotBytes >> 4);
            mbar_wait(s_bar + 32 * rv.slot + 8, rv.phase);
            turn_begin();
            wgmma_fence();
#pragma unroll
            for (int ks = 0; ks < 4; ks++) wgmma_n64<1>(ob, p + ks * 4, lo + 64 + ks * 256, kDescHi, 1);
#pragma unroll
            for (int ks = 0; ks < 4; ks++) wgmma_n64<1>(oa, p + ks * 4, lo + ks * 256, kDescHi, 1);
            wgmma_commit();
            turn_end();
            rv.advance();
        };
        asm volatile("st.shared.v2.f32 [%0], {%1, %2};" ::"r"(stg + lane * 8), "f"(l0), "f"(l1) : "memory");
        pv_tile(p);
        float4 la, lb;
        asm volatile("ld.shared.v4.f32 {%0, %1, %2, %3}, [%4];" : "=f"(la.x), "=f"(la.y), "=f"(la.z), "=f"(la.w)
                     : "r"(stg + (lane >> 2) * 32) : "memory");
        asm volatile("ld.shared.v4.f32 {%0, %1, %2, %3}, [%4];" : "=f"(lb.x), "=f"(lb.y), "=f"(lb.z), "=f"(lb.w)
                     : "r"(stg + (lane >> 2) * 32 + 16) : "memory");
        float i0 = (la.x + la.z) + (lb.x + lb.z), i1 = (la.y + la.w) + (lb.y + lb.w);
        asm("rcp.approx.ftz.f32 %0, %0;" : "+f"(i0));
        asm("rcp.approx.ftz.f32 %0, %0;" : "+f"(i1));
        mbar_arrive_if(s_bar, i0 + i1 < 0.f);
        if (kSplit < 3) pv_tile(p2);
        auto pv_piece = [&](int j, const uint32_t (&p)[16], float (&d)[32]) {
            const uint32_t lo = desc_base + (kSlotBytes >> 4) + rv.slot * (2 * kSlotBytes >> 4) + (j & 1) * 512;
            mbar_wait(s_bar_last + 8 * j, 0);
            wg1_sync(6 + j, wg);
            wgmma_fence();
#pragma unroll
            for (int ks = 0; ks < 4; ks++)
                wgmma_n64<1>(d, p + ks * 4, lo + ks * 128, (1024u >> 4) | (1u << 30), 1);
            wgmma_commit();
            if (j < 2 * kSplit - 1) wg0_arrive(6 + j, wg);
            if (j & 1) rv.advance();
        };
        auto stage_rows = [&](int half, int r, const float (&d)[32]) {
            const float a = r ? i1 : i0;
#pragma unroll
            for (int i = 0; i < 2; i++) {
                const float* y = d + 16 * i + 2 * r;
                asm volatile("stmatrix.sync.aligned.m8n8.x4.shared.b16 [%0], {%1, %2, %3, %4};"
                             ::"r"((st_addr ^ (64 * i)) + half * 8192 + r * 1024), "r"(pack_bf16(y[0] * a, y[1] * a)),
                             "r"(pack_bf16(y[4] * a, y[5] * a)), "r"(pack_bf16(y[8] * a, y[9] * a)),
                             "r"(pack_bf16(y[12] * a, y[13] * a)) : "memory");
            }
        };
        if (kSplit > 2) pv_piece(0, p2, oa);
        pv_piece(kSplit - 2, p1, oa);
        pv_piece(kSplit - 1, p0, oa);
        wgmma_wait<0>();
        fence_regs(oa);
        stage_rows(0, 0, oa);
        stage_rows(0, 1, oa);
        asm volatile("bar.arrive %0, 160;" ::"r"(2 + wg) : "memory");
        fence_regs(ob);
        if (kSplit > 2) pv_piece(3, p2, ob);
        pv_piece(2 * kSplit - 2, p1, ob);
        pv_piece(2 * kSplit - 1, p0, ob);
        wgmma_wait<0>();
        fence_regs(ob);
        char* dst = reinterpret_cast<char*>(out) + out_off;
#pragma unroll
        for (int r = 0; r < 2; r++) {
            stage_rows(1, r, ob);
            if (r == 0) wg0_arrive(5 + 2 * kSplit, wg);
            __syncwarp();
#pragma unroll
            for (int i = 2 * r; i < 2 * r + 2; i++) {
                uint4 v;
                asm volatile("ld.shared.v4.b32 {%0, %1, %2, %3}, [%4];" : "=r"(v.x), "=r"(v.y), "=r"(v.z), "=r"(v.w)
                             : "r"((ld_addr ^ (64 * (i & 1))) + i * 512 + 8192) : "memory");
                asm volatile("st.global.v4.b32 [%0], {%1, %2, %3, %4};" ::"l"(dst + i * 1024 + 128),
                             "r"(v.x), "r"(v.y), "r"(v.z), "r"(v.w) : "memory");
            }
        }
    }
}

typedef CUresult (*EncodeTiledFn)(CUtensorMap*, CUtensorMapDataType, cuuint32_t, void*, const cuuint64_t*,
                                  const cuuint64_t*, const cuuint32_t*, const cuuint32_t*, CUtensorMapInterleave,
                                  CUtensorMapSwizzle, CUtensorMapL2promotion, CUtensorMapFloatOOBfill);

}

extern "C" void kernel_launch(void* const* d_in, const int* in_sizes, int n_in, void* d_out, int out_size) {
    (void)n_in; (void)out_size;
    const int num_phys = in_sizes[1] / (kPage * kHkv * kD);

    static EncodeTiledFn encode = nullptr;
    static unsigned* progress = nullptr;
    static float tile_ns = 0.f;
    if (!encode) {
        int dev = 0, khz = 0, bits = 0;
        cudaGetDevice(&dev);
        cudaDeviceGetAttribute(&khz, cudaDevAttrMemoryClockRate, dev);
        cudaDeviceGetAttribute(&bits, cudaDevAttrGlobalMemoryBusWidth, dev);
        const float peak_gbs = 2.f * (float)khz * (float)(bits / 8) * 1e-6f;
        tile_ns = 2 * kSlotBytes / (kDramEfficiency * (peak_gbs > 0.f ? peak_gbs : 3352.f));
        cudaGetSymbolAddress((void**)&progress, g_progress);
        cudaDriverEntryPointQueryResult qr;
        cudaGetDriverEntryPoint("cuTensorMapEncodeTiled", (void**)&encode, cudaEnableDefault, &qr);
        cudaFuncSetAttribute(paged_attn_kernel, cudaFuncAttributeMaxDynamicSharedMemorySize, kSmemBytes);
    }
    Maps tm;
    auto cache_map = [&](CUtensorMap* map, void* cache, cuuint32_t halves, cuuint32_t groups) {
        const cuuint64_t dim[4] = {64, 8, 2 * kHkv, (cuuint64_t)num_phys * 2};
        const cuuint64_t str[3] = {kHkv * kD * 2, 128, 8 * kHkv * kD * 2};
        const cuuint32_t box[4] = {64, 8, halves, groups};
        const cuuint32_t es[4] = {1, 1, 1, 1};
        encode(map, CU_TENSOR_MAP_DATA_TYPE_BFLOAT16, 4, cache, dim, str, box, es, CU_TENSOR_MAP_INTERLEAVE_NONE,
               CU_TENSOR_MAP_SWIZZLE_128B, CU_TENSOR_MAP_L2_PROMOTION_L2_128B, CU_TENSOR_MAP_FLOAT_OOB_FILL_NONE);
    };
    for (int kv = 0; kv < 2; kv++) {
        cache_map(&tm.page[kv], d_in[1 + kv], 2, 2);
        cache_map(&tm.group[kv], d_in[1 + kv], 2, 1);
    }
    cache_map(&tm.vhalf, d_in[2], 1, 2);
    {
        const cuuint64_t dim[2] = {kD, (cuuint64_t)kB * kHkv * kRows};
        const cuuint64_t str[1] = {kD * 2};
        const cuuint32_t box[2] = {64, kRows};
        const cuuint32_t es[2] = {1, 1};
        encode(&tm.q, CU_TENSOR_MAP_DATA_TYPE_BFLOAT16, 2, d_in[0], dim, str, box, es, CU_TENSOR_MAP_INTERLEAVE_NONE,
               CU_TENSOR_MAP_SWIZZLE_128B, CU_TENSOR_MAP_L2_PROMOTION_L2_128B, CU_TENSOR_MAP_FLOAT_OOB_FILL_NONE);
        const cuuint32_t obox[2] = {64, 64};
        encode(&tm.out, CU_TENSOR_MAP_DATA_TYPE_BFLOAT16, 2, d_out, dim, str, obox, es, CU_TENSOR_MAP_INTERLEAVE_NONE,
               CU_TENSOR_MAP_SWIZZLE_128B, CU_TENSOR_MAP_L2_PROMOTION_NONE, CU_TENSOR_MAP_FLOAT_OOB_FILL_NONE);
    }
    paged_attn_kernel<<<kB * kHkv, kThreads, kSmemBytes>>>(
        (const int*)d_in[4], (const int*)d_in[3], (const __nv_bfloat16*)d_in[0], (__nv_bfloat16*)d_out, progress,
        num_phys * 2, tile_ns, tm);
}
```

```cpp
#include <cuda_runtime.h>
#include <cuda.h>
#include <cuda_bf16.h>
#include <stdint.h>

namespace {

constexpr int kB = 16, kHkv = 8, kD = 128, kPage = 16, kNBPS = 256;
constexpr int kRows = 128;
constexpr int kSkv = kNBPS * kPage;
constexpr int kTileN = 64;
constexpr int kSlotBytes = 16384;
constexpr int kStages = 6;
constexpr float kDramEfficiency = 0.972f;
constexpr float kWindow = 1880.f;
constexpr float kTaper = 1020.f;
constexpr float kTaperSpan = 9900.f;
constexpr float kAheadK = 85.f, kAheadV = 210.f;
constexpr float kAheadR1 = 170.f, kAheadR0 = 55.f;
constexpr float kTightR0 = 0.16f;
constexpr float kStoreLead = 660.f, kStoreStagger = 0.175f;
constexpr float kStartLag = 540.f;
constexpr float kClockGain = 0.28f;
constexpr float kClockStep = 800.f;
constexpr unsigned kClockWarmup = 200;
constexpr int kLead = 4;
constexpr int kSplit = 3;
constexpr int kEvenTiles = 5;
constexpr int kQPrefetch = 16384;
constexpr float kMaxGrowth = 4096.f;
constexpr int kThreads = 384;

constexpr int kSmemRing = kStages * 2 * kSlotBytes;
constexpr int kSortWords = 160;
constexpr int kSmemHead = 4096;
constexpr int kSmemBytes = 1024 + kSmemHead + kSmemRing;

__device__ __forceinline__ uint32_t smem_u32(const void* p) {
    return (uint32_t)__cvta_generic_to_shared(p);
}
__device__ __forceinline__ void mbar_init(uint32_t bar, uint32_t cnt) {
    asm volatile("mbarrier.init.shared::cta.b64 [%0], %1;" ::"r"(bar), "r"(cnt) : "memory");
}
__device__ __forceinline__ void mbar_expect_tx(uint32_t bar, uint32_t bytes) {
    asm volatile("mbarrier.arrive.expect_tx.shared::cta.b64 _, [%0], %1;" ::"r"(bar), "r"(bytes) : "memory");
}
__device__ __forceinline__ void mbar_arrive_if(uint32_t bar, bool pred) {
    asm volatile("{\n.reg .pred p;\nsetp.ne.u32 p, %1, 0;\n@p mbarrier.arrive.shared::cta.b64 _, [%0];\n}"
                 ::"r"(bar), "r"((uint32_t)pred) : "memory");
}
__device__ __forceinline__ void mbar_wait(uint32_t bar, uint32_t parity) {
    asm volatile(
        "{\n.reg .pred p;\n"
        "WAIT_LOOP:\n"
        "mbarrier.try_wait.parity.shared::cta.b64 p, [%0], %1;\n"
        "@p bra WAIT_DONE;\n"
        "bra WAIT_LOOP;\n"
        "WAIT_DONE:\n}" ::"r"(bar), "r"(parity) : "memory");
}
__device__ __forceinline__ void tma_page(uint32_t dst, const CUtensorMap* tm, uint32_t bar, int c2, int c3, uint64_t pol) {
    asm volatile(
        "cp.async.bulk.tensor.4d.shared::cluster.global.mbarrier::complete_tx::bytes.L2::cache_hint"
        " [%0], [%1, {%3, %3, %4, %5}], [%2], %6;"
        ::"r"(dst), "l"(tm), "r"(bar), "r"(0), "r"(c2), "r"(c3), "l"(pol) : "memory");
}
__device__ __forceinline__ void tma_group(uint32_t dst, const CUtensorMap* tm, uint32_t bar, int c1, int c2, int c3, uint64_t pol) {
    asm volatile(
        "cp.async.bulk.tensor.4d.shared::cluster.global.mbarrier::complete_tx::bytes.L2::cache_hint"
        " [%0], [%1, {%3, %4, %5, %6}], [%2], %7;"
        ::"r"(dst), "l"(tm), "r"(bar), "r"(0), "r"(c1), "r"(c2), "r"(c3), "l"(pol) : "memory");
}
__device__ __forceinline__ void tma_2d(uint32_t dst, const CUtensorMap* tm, uint32_t bar, int c0, int c1) {
    asm volatile(
        "cp.async.bulk.tensor.2d.shared::cluster.global.mbarrier::complete_tx::bytes"
        " [%0], [%1, {%3, %4}], [%2];" ::"r"(dst), "l"(tm), "r"(bar), "r"(c0), "r"(c1)
        : "memory");
}
__device__ __forceinline__ int4 ldg_v4(const int4* p) {
    int4 v;
    asm volatile("ld.global.nc.v4.b32 {%0, %1, %2, %3}, [%4];" : "=r"(v.x), "=r"(v.y), "=r"(v.z), "=r"(v.w) : "l"(p) : "memory");
    return v;
}
__device__ __forceinline__ bool elect_one() {
    uint32_t pred;
    asm volatile("{\n.reg .pred p;\nelect.sync _|p, 0xffffffff;\nselp.u32 %0, 1, 0, p;\n}" : "=r"(pred));
    return pred;
}
__device__ __forceinline__ void wg1_sync(int id, int wg) {
    asm volatile("{\n.reg .pred p;\nsetp.ne.u32 p, %1, 0;\n@p bar.sync %0, 256;\n}" ::"r"(id), "r"(wg) : "memory");
}
__device__ __forceinline__ void wg0_arrive(int id, int wg) {
    asm volatile("{\n.reg .pred p;\nsetp.eq.u32 p, %1, 0;\n@p bar.arrive %0, 256;\n}" ::"r"(id), "r"(wg) : "memory");
}
__device__ __forceinline__ void wgmma_fence() { asm volatile("wgmma.fence.sync.aligned;" ::: "memory"); }
__device__ __forceinline__ void wgmma_commit() { asm volatile("wgmma.commit_group.sync.aligned;" ::: "memory"); }
template <int N>
__device__ __forceinline__ void wgmma_wait() { asm volatile("wgmma.wait_group.sync.aligned %0;" ::"n"(N) : "memory"); }
template <int N>
__device__ __forceinline__ void fence_regs(float (&r)[N]) {
#pragma unroll
    for (int i = 0; i < N; i++) asm volatile("" : "+f"(r[i])::"memory");
}
template <int N>
__device__ __forceinline__ void fence_regs(uint32_t (&r)[N]) {
#pragma unroll
    for (int i = 0; i < N; i++) asm volatile("" : "+r"(r[i])::"memory");
}
__device__ __forceinline__ float ex2(float x) {
    float y;
    asm("ex2.approx.ftz.f32 %0, %1;" : "=f"(y) : "f"(x));
    return y;
}
__device__ __forceinline__ uint32_t pack_bf16(float lo, float hi) {
    uint32_t r;
    asm("cvt.rn.bf16x2.f32 %0, %1, %2;" : "=r"(r) : "f"(hi), "f"(lo));
    return r;
}

__device__ __forceinline__ void scale_bf16(uint32_t& p, float a) {
    p = pack_bf16(__uint_as_float(p << 16) * a, __uint_as_float(p & 0xffff0000u) * a);
}

template <int TB>
__device__ __forceinline__ void wgmma_n64(float (&d)[32], const uint32_t* a, uint32_t desc_lo, uint32_t desc_hi, int scale_d) {
    asm volatile(
        "{\n.reg .pred p;\n.reg .b64 db;\n"
        "setp.ne.b32 p, %38, 0;\n"
        "mov.b64 db, {%36, %37};\n"
        "wgmma.mma_async.sync.aligned.m64n64k16.f32.bf16.bf16 "
        "{%0, %1, %2, %3, %4, %5, %6, %7, %8, %9, %10, %11, %12, %13, %14, %15, "
        "%16, %17, %18, %19, %20, %21, %22, %23, %24, %25, %26, %27, %28, %29, %30, %31}, "
        "{%32, %33, %34, %35}, db, p, 1, 1, %39;\n}"
        : "+f"(d[0]), "+f"(d[1]), "+f"(d[2]), "+f"(d[3]), "+f"(d[4]), "+f"(d[5]), "+f"(d[6]), "+f"(d[7]),
          "+f"(d[8]), "+f"(d[9]), "+f"(d[10]), "+f"(d[11]), "+f"(d[12]), "+f"(d[13]), "+f"(d[14]), "+f"(d[15]),
          "+f"(d[16]), "+f"(d[17]), "+f"(d[18]), "+f"(d[19]), "+f"(d[20]), "+f"(d[21]), "+f"(d[22]), "+f"(d[23]),
          "+f"(d[24]), "+f"(d[25]), "+f"(d[26]), "+f"(d[27]), "+f"(d[28]), "+f"(d[29]), "+f"(d[30]), "+f"(d[31])
        : "r"(a[0]), "r"(a[1]), "r"(a[2]), "r"(a[3]), "r"(desc_lo), "r"(desc_hi), "r"(scale_d), "n"(TB));
}
__device__ __forceinline__ void wgmma_pv(float (&d)[64], const uint32_t* a, uint32_t desc_lo, uint32_t desc_hi, int scale_d) {
    asm volatile(
        "{\n.reg .pred p;\n.reg .b64 db;\n"
        "setp.ne.b32 p, %70, 0;\n"
        "mov.b64 db, {%68, %69};\n"
        "wgmma.mma_async.sync.aligned.m64n128k16.f32.bf16.bf16 "
        "{%0, %1, %2, %3, %4, %5, %6, %7, %8, %9, %10, %11, %12, %13, %14, %15, "
        "%16, %17, %18, %19, %20, %21, %22, %23, %24, %25, %26, %27, %28, %29, %30, %31, "
        "%32, %33, %34, %35, %36, %37, %38, %39, %40, %41, %42, %43, %44, %45, %46, %47, "
        "%48, %49, %50, %51, %52, %53, %54, %55, %56, %57, %58, %59, %60, %61, %62, %63}, "
        "{%64, %65, %66, %67}, db, p, 1, 1, 1;\n}"
        : "+f"(d[0]), "+f"(d[1]), "+f"(d[2]), "+f"(d[3]), "+f"(d[4]), "+f"(d[5]), "+f"(d[6]), "+f"(d[7]),
          "+f"(d[8]), "+f"(d[9]), "+f"(d[10]), "+f"(d[11]), "+f"(d[12]), "+f"(d[13]), "+f"(d[14]), "+f"(d[15]),
          "+f"(d[16]), "+f"(d[17]), "+f"(d[18]), "+f"(d[19]), "+f"(d[20]), "+f"(d[21]), "+f"(d[22]), "+f"(d[23]),
          "+f"(d[24]), "+f"(d[25]), "+f"(d[26]), "+f"(d[27]), "+f"(d[28]), "+f"(d[29]), "+f"(d[30]), "+f"(d[31]),
          "+f"(d[32]), "+f"(d[33]), "+f"(d[34]), "+f"(d[35]), "+f"(d[36]), "+f"(d[37]), "+f"(d[38]), "+f"(d[39]),
          "+f"(d[40]), "+f"(d[41]), "+f"(d[42]), "+f"(d[43]), "+f"(d[44]), "+f"(d[45]), "+f"(d[46]), "+f"(d[47]),
          "+f"(d[48]), "+f"(d[49]), "+f"(d[50]), "+f"(d[51]), "+f"(d[52]), "+f"(d[53]), "+f"(d[54]), "+f"(d[55]),
          "+f"(d[56]), "+f"(d[57]), "+f"(d[58]), "+f"(d[59]), "+f"(d[60]), "+f"(d[61]), "+f"(d[62]), "+f"(d[63])
        : "r"(a[0]), "r"(a[1]), "r"(a[2]), "r"(a[3]), "r"(desc_lo), "r"(desc_hi), "r"(scale_d));
}

__device__ __forceinline__ int bcast(int v, int lane, int src) {
    return __reduce_max_sync(~0u, lane == src ? v : 0);
}

__device__ __forceinline__ void sort_pages(const int4& row0, const int4& row1, int first, int n, int lane,
                                           uint32_t s_list, uint32_t s_bits) {
    constexpr int kW = kSortWords / 32;
    const uint32_t e[8] = {(uint32_t)row0.x, (uint32_t)row0.y, (uint32_t)row0.z, (uint32_t)row0.w,
                           (uint32_t)row1.x, (uint32_t)row1.y, (uint32_t)row1.z, (uint32_t)row1.w};
    uint32_t wa[8];
#pragma unroll
    for (int i = 0; i < 8; i++) {
        const bool use = (unsigned)(lane - first + (i >> 2) * 32) < (unsigned)n && e[i] < kSortWords * 32;
        wa[i] = s_bits + (use ? e[i] >> 5 : 0) * 8;
        asm volatile("{\n.reg .pred p;\nsetp.ne.u32 p, %2, 0;\n@p red.shared.or.b32 [%0], %1;\n}"
                     ::"r"(wa[i]), "r"(1u << (e[i] & 31)), "r"((uint32_t)use) : "memory");
    }
    __syncwarp();
    uint32_t cnt[kW + 1];
    cnt[0] = 0;
#pragma unroll
    for (int i = 0; i < kW; i++) {
        uint32_t w;
        asm volatile("ld.shared.b32 %0, [%1];" : "=r"(w) : "r"(s_bits + (lane * kW + i) * 8) : "memory");
        cnt[i + 1] = cnt[i] + __popc(w);
    }
    uint32_t scan = cnt[kW];
#pragma unroll
    for (int o = 1; o < 32; o <<= 1) {
        const uint32_t v = __shfl_up_sync(~0u, scan, o);
        if (lane >= o) scan += v;
    }
    const bool sorted = __shfl_sync(~0u, scan, 31) == (uint32_t)n * 4;
#pragma unroll
    for (int i = 0; i < kW; i++)
        asm volatile("st.shared.b32 [%0], %1;" ::"r"(s_bits + (lane * kW + i) * 8 + 4), "r"(scan - cnt[kW] + cnt[i]) : "memory");
    __syncwarp();
#pragma unroll
    for (int i = 0; i < 8; i++) {
        uint32_t w, base;
        asm volatile("ld.shared.v2.b32 {%0, %1}, [%2];" : "=r"(w), "=r"(base) : "r"(wa[i]) : "memory");
        wa[i] = base + __popc(w & ((1u << (e[i] & 31)) - 1));
    }
#pragma unroll
    for (int i = 0; i < 8; i++) {
        const uint32_t pos = sorted ? wa[i] : (lane - first) * 4 + (i >> 2) * 128 + (i & 3);
        asm volatile("{\n.reg .pred p;\nsetp.ne.u32 p, %2, 0;\n@p st.shared.b32 [%0], %1;\n}"
                     ::"r"(s_list + pos * 4), "r"(e[i] * 2), "r"((uint32_t)((unsigned)(lane - first + (i >> 2) * 32) < (unsigned)n)) : "memory");
    }
}

__device__ unsigned g_progress;

struct Maps {
    CUtensorMap page[2];
    CUtensorMap group[2];
    CUtensorMap vhalf;
    CUtensorMap q;
    CUtensorMap out;
};

struct Ring {
    int slot;
    uint32_t phase;
    __device__ __forceinline__ void advance() {
        if (++slot == kStages) { slot = 0; phase ^= 1; }
    }
};

__global__ void __launch_bounds__(kThreads, 1)
paged_attn_kernel(const int* __restrict__ ctx, const int* __restrict__ table, const __nv_bfloat16* __restrict__ q,
                  __nv_bfloat16* __restrict__ out, unsigned* progress, int oob_coord, float tile_ns,
                  const __grid_constant__ Maps tm) {
    extern __shared__ uint8_t smem_raw[];
    const int tid = threadIdx.x, lane = tid & 31;
    const int b = blockIdx.x / kHkv, h = blockIdx.x % kHkv;
    const int bh = b * kHkv + h;
    const __nv_bfloat16* q_tile = q + (size_t)bh * kRows * kD;
    if (elect_one()) asm volatile("cp.async.bulk.prefetch.L2.global [%0], %1;" ::"l"(q_tile), "r"(16) : "memory");
    if (tid == 0) asm volatile("cp.async.bulk.prefetch.L2.global [%0], %1;" ::"l"(q_tile), "r"(kQPrefetch) : "memory");
    uint32_t t_begin;
    asm volatile("mov.u32 %0, %globaltimer_lo;" : "=r"(t_begin) :: "memory");
    int cl;
    int4 row0, row1;
    if (tid >= 256) {
        const bool head = tid >> 5 == 10;
        const int4* row = reinterpret_cast<const int4*>(table + b * kNBPS) + (head ? 0 : lane);
        row0 = ldg_v4(row);
        asm volatile("ld.global.nc.b32 %0, [%1];" : "=r"(cl) : "l"(ctx + (lane & (kB - 1))) : "memory");
        row1 = ldg_v4(row + (head ? 0 : 32));
    }
    const int warp = __shfl_sync(~0u, tid >> 5, 0);
    const uint32_t sbase = __reduce_max_sync(~0u, (smem_u32(smem_raw) + 1023 + kSmemHead) & ~1023u);
    const uint32_t s_bits = sbase - 4096, s_list = sbase - 2048;
    const uint32_t s_bar = sbase - 1024, s_clock = sbase - 512;
    const uint32_t s_bar_last = s_bar + 32 * kStages;
    static_assert(kStages == 6 && kLead == 4 && kSplit == 3, "barrier layout, code of the last tiles");

    if (warp < 8) {
        if (elect_one()) {
            mbar_init(s_bar + 32 * warp, 1);
            mbar_init(s_bar + 32 * warp + 8, 1);
            mbar_init(s_bar + 32 * warp + 16, warp < kStages ? 9 : 1);
            mbar_init(s_bar + 32 * warp + 24, warp < kStages ? 8 : 1);
            asm volatile("fence.mbarrier_init.release.cluster;" ::: "memory");
            if (warp < 2 || warp >= kStages) {
                mbar_expect_tx(s_bar + 32 * warp, warp < 2 ? kSlotBytes : kSlotBytes / 2);
                mbar_expect_tx(s_bar + 32 * warp + 8, warp < 2 ? kSlotBytes : kSlotBytes / 2);
            }
            if (warp >= kStages) {
                mbar_expect_tx(s_bar + 32 * warp + 16, kSlotBytes / 2);
                mbar_expect_tx(s_bar + 32 * warp + 24, kSlotBytes / 2);
            }
            if (warp == 0) {
                asm volatile("fence.proxy.async.shared::cta;" ::: "memory");
                tma_2d(sbase, &tm.q, s_bar, 0, bh * kRows);
                tma_2d(sbase + kSlotBytes, &tm.q, s_bar + 8, 64, bh * kRows);
            }
        }
    } else if (warp == 8) {
#pragma unroll
        for (int i = 0; i < kSortWords / 32; i++)
            asm volatile("st.shared.b32 [%0], %1;" ::"r"(s_bits + (lane * (kSortWords / 32) + i) * 8), "r"(0) : "memory");
    }
    __syncthreads();

    if (warp >= 8) {
        asm volatile("setmaxnreg.dec.sync.aligned.u32 40;");
        const int kv = (warp >> 1) & 1;
        uint64_t pol;
        asm volatile("createpolicy.fractional.L2::evict_first.b64 %0, 1.0;" : "=l"(pol));
        const int len_l = cl <= 0 ? kSkv : min(cl, kSkv);
        const int len = bcast(len_l, lane, b);
        const int top = (len - 1) / kTileN;
        const int n = max(top, kLead - 1);
        const int early = top > kLead;
        if (warp == 10 && early && elect_one()) {
#pragma unroll
            for (int i = 0; i < 2; i++) {
                const uint32_t dst = sbase + (4 + i) * kSlotBytes, bar = s_bar + 64 + 8 * i;
                mbar_expect_tx(bar, kSlotBytes);
                tma_page(dst, &tm.page[i], bar, h * 2, row0.x * 2, pol);
                tma_page(dst + 4096, &tm.page[i], bar, h * 2, row0.y * 2, pol);
                tma_page(dst + 8192, &tm.page[i], bar, h * 2, row0.z * 2, pol);
                tma_page(dst + 12288, &tm.page[i], bar, h * 2, row0.w * 2, pol);
            }
        }
        if (warp & 1) {
            const int4 src = top < 32 ? row0 : row1;
            const int p0 = bcast(src.x, lane, top & 31) * 2, p1 = bcast(src.y, lane, top & 31) * 2;
            const int p2 = bcast(src.z, lane, top & 31) * 2, p3 = bcast(src.w, lane, top & 31) * 2;
            const int rem = len - top * kTileN, full = (rem - 1) / kPage, r = rem - full * kPage;
            const int last = full == 0 ? p0 : full == 1 ? p1 : full == 2 ? p2 : p3;
            const uint32_t off = (3 - full) * 4096;
            if (elect_one()) {
                const uint32_t dst = sbase + (2 + kv) * kSlotBytes, bar = s_bar + 32 + 8 * kv;
                tma_page(dst + ((off + 4096) & 0x3fff), &tm.page[kv], bar, h * 2, full > 0 ? p0 : oob_coord, pol);
                tma_page(dst + ((off + 8192) & 0x3fff), &tm.page[kv], bar, h * 2, full > 1 ? p1 : oob_coord, pol);
                tma_page(dst + ((off + 12288) & 0x3fff), &tm.page[kv], bar, h * 2, full > 2 ? p2 : oob_coord, pol);
                tma_group(dst + off, &tm.group[kv], bar, r - 16, h * 2, last + 1, pol);
                tma_group(dst + off + 2048, &tm.group[kv], bar, min(r - 8, 0), h * 2, last, pol);
                asm volatile("prefetch.tensormap [%0];" ::"l"(kv ? &tm.vhalf : &tm.out) : "memory");
            }
            {
                __syncwarp();
                asm volatile("bar.sync %0, 192;" ::"r"(2 + kv) : "memory");
                asm volatile("fence.proxy.async.shared::cta;" ::: "memory");
                if (elect_one()) {
                    asm volatile("cp.async.bulk.tensor.2d.global.shared::cta.bulk_group [%0, {%1, %2}], [%3];"
                                 ::"l"(&tm.out), "r"(0), "r"(bh * kRows + kv * 64),
                                 "r"(sbase + ((n + 3) % kStages * 2 + kv) * kSlotBytes) : "memory");
                    asm volatile("cp.async.bulk.commit_group;" ::: "memory");
                }
            }
            asm volatile("cp.async.bulk.wait_group.read 0;" ::: "memory");
            return;
        }
        const int full_l = lane < kB ? (len_l - 1) / kTileN : 0;
        const float t_all = (float)(__reduce_add_sync(~0u, full_l) * kHkv) * tile_ns;
        float origin = (kB * kHkv + __reduce_add_sync(~0u, lane < kB ? len_l - full_l * kTileN : 0) * (1.f / 8)) * tile_ns + kStartLag;
        if (warp == 10) {
            if (lane == 0) {
                const float gain = fminf(__fdividef(kClockGain * t_all, (float)(n * kB * kHkv) * tile_ns), 0.5f);
                mbar_arrive_if(s_bar + 16, true);
                mbar_arrive_if(s_bar + 48, true);
                Ring m{2, 0};
                unsigned g;
#pragma unroll 1
                for (int t = n - 1; t >= kLead - 2; t--) {
                    if (t == kLead - 2) m.advance();
                    mbar_wait(s_bar + 32 * m.slot, m.phase);
                    mbar_arrive_if(s_bar + 32 * m.slot + 16, true);
                    m.advance();
                    uint32_t now;
                    asm volatile("mov.u32 %0, %globaltimer_lo;" : "=r"(now) :: "memory");
                    asm volatile("atom.relaxed.gpu.global.add.u32 %0, [%1], 1;" : "=r"(g) : "l"(progress) : "memory");
                    g &= 0xfffff;
                    const float d = (float)(int)(now - t_begin) - (float)g * tile_ns - origin;
                    if (g >= kClockWarmup) origin = fmaf(fminf(d, kClockStep), gain, origin);
                    asm volatile("st.volatile.shared.b32 [%0], %1;" ::"r"(s_clock), "r"(t_begin + (int)origin) : "memory");
                }
                asm volatile("atom.relaxed.gpu.global.add.u32 %0, [%1], 0x100000;" : "=r"(g) : "l"(progress) : "memory");
                if ((g >> 20) == kB * kHkv - 1) asm volatile("st.relaxed.gpu.global.u32 [%0], 0;" ::"l"(progress) : "memory");
            }
            return;
        }
        asm volatile("st.volatile.shared.b32 [%0], %1;" ::"r"(s_clock), "r"(t_begin + (int)origin) : "memory");
        if (lane < 4 * (kLead - 1)) asm volatile("st.shared.b32 [%0], %1;" ::"r"(s_list + lane * 4), "r"(oob_coord) : "memory");
        sort_pages(row0, row1, early, top - early, lane, s_list, s_bits);
        __syncwarp();
        auto pages = [&](int t) {
            int4 pg;
            asm volatile("ld.shared.v4.b32 {%0, %1, %2, %3}, [%4];" : "=r"(pg.x), "=r"(pg.y), "=r"(pg.z), "=r"(pg.w)
                         : "r"(s_list + t * 16) : "memory");
            return pg;
        };
        const float dt_end = tile_ns * (kB * kHkv / 2);
        const float stagger = dt_end * ((b * 7 % kB) + 0.5f) * (1.f / kB);
        const float dt = __fdividef(t_all - dt_end * (2 * kEvenTiles), (float)(2 * max(n - kEvenTiles, 1)));
        float left = (n > kEvenTiles ? t_all : dt_end * (float)(2 * n)) - stagger;
        auto wait_due = [&](float step, float ahead = 0.f) {
            const int due = (int)(t_all - kWindow - left + fmaxf(fmaf(left, -kTaper / kTaperSpan, kTaper), 0.f) - ahead);
            left -= step;
#pragma unroll 1
            while (true) {
                uint32_t now, org;
                asm volatile("ld.volatile.shared.b32 %0, [%1];" : "=r"(org) : "r"(s_clock) : "memory");
                asm volatile("mov.u32 %0, %globaltimer_lo;" : "=r"(now));
                const int wait = due - (int)(now - org);
                if (wait <= 0) break;
                if (wait > 64) __nanosleep(min(wait >> 1, 200));
            }
        };
        auto acquire = [&](const Ring& r, int kv, float step, float ahead = 0.f) {
            const uint32_t bar = s_bar + 32 * r.slot + 8 * kv;
            mbar_wait(bar + 16, r.phase ^ 1);
            if (lane == 0) mbar_expect_tx(bar, kSlotBytes);
            wait_due(step, ahead);
            return bar;
        };
        auto load4 = [&](uint32_t dst, uint32_t stride, const CUtensorMap* map, uint32_t bar, int c2, const int4& pg) {
            if (elect_one()) {
                tma_page(dst, map, bar, c2, pg.x, pol);
                tma_page(dst + stride, map, bar, c2, pg.y, pol);
                tma_page(dst + 2 * stride, map, bar, c2, pg.z, pol);
                tma_page(dst + 3 * stride, map, bar, c2, pg.w, pol);
            }
        };
        Ring r{2 + early, 0};
        if (early) left -= 2.f * (n > kEvenTiles ? dt : dt_end);
#pragma unroll 1
        for (int t = n - 1 - early; t >= kLead; t--) {
            const int4 pg = pages(t);
            const uint32_t dst = sbase + 2 * r.slot * kSlotBytes;
            const float step = t < kEvenTiles ? dt_end : dt;
            load4(dst, 4096, &tm.page[0], acquire(r, 0, step), h * 2, pg);
            load4(dst + kSlotBytes, 4096, &tm.page[1], acquire(r, 1, step), h * 2, pg);
            r.advance();
        }
        Ring rv = r;
#pragma unroll 1
        for (int i = 0; i < 2 * kLead - kSplit; i++) {
            const int kv = i >= kLead;
            const int t = (kv ? 2 * kLead : kLead) - 1 - i;
            if (t >= n) continue;
            const int4 pg = pages(t);
            const Ring cur = kv ? rv : r;
            load4(sbase + (2 * cur.slot + kv) * kSlotBytes, 4096, &tm.page[kv],
                  acquire(cur, kv, dt_end, kv ? kAheadV : i ? kAheadK : 0.f), h * 2, pg);
            if (kv) rv.advance(); else r.advance();
        }
        left += 0.5f * stagger;
#pragma unroll 1
        for (int j = 0; j < 2 * kSplit; j++) {
            const int half = j >= kSplit, t = (half ? 2 * kSplit : kSplit) - 1 - j;
            const int4 pg = pages(t);
            mbar_wait(s_bar + 32 * rv.slot + 24, rv.phase ^ 1);
            wait_due(0.5f * dt_end, !half || t > 1 ? kAheadV : t ? kAheadR1 : fmaf(stagger, kTightR0, kAheadR0));
            load4(sbase + (2 * rv.slot + 1) * kSlotBytes + (j & 1) * 8192, 2048, &tm.vhalf, s_bar_last + 8 * j, h * 2 + half, pg);
            if (j & 1) rv.advance();
        }
        uint32_t due, now, landed;
        asm volatile("ld.volatile.shared.b32 %0, [%1];" : "=r"(due) : "r"(s_clock) : "memory");
        due += (int)(t_all - kStoreLead + kStoreStagger * stagger);
#pragma unroll 1
        do {
            asm volatile("{\n.reg .pred p;\nmbarrier.test_wait.parity.shared::cta.b64 p, [%1], 0;\nselp.u32 %0, 1, 0, p;\n}"
                         : "=r"(landed) : "r"(s_bar_last + 8 * (2 * kSplit - 2)) : "memory");
            asm volatile("mov.u32 %0, %globaltimer_lo;" : "=r"(now));
        } while (!landed && (int)(due - now) > 0);
        __syncwarp();
        asm volatile("bar.arrive 2, 192;" ::: "memory");
        asm volatile("bar.arrive 3, 192;" ::: "memory");
    } else {
        asm volatile("setmaxnreg.inc.sync.aligned.u32 232;");
        const int wg = warp >> 2;
        const int clb = __reduce_max_sync(~0u, __ldg(ctx + b));
        const int len = clb <= 0 ? kSkv : min(clb, kSkv);
        const int top = (len - 1) / kTileN;
        const float c = clb <= 0 ? 0.f : 0.08838834764831845f * 1.4426950408889634f;

        if (wg == 1) asm volatile("bar.arrive 4, 256;" ::: "memory");
        constexpr uint32_t kDescHi = (2048u >> 4) | (1u << 30);
        constexpr uint32_t kLboK = 1u << 16, kLboV = (1024u >> 4) << 16;
        const uint32_t desc_base = (sbase & 0x3FFFF) >> 4;

        const uint32_t stg = sbase + (max(top, kLead - 1) + 3) % kStages * 2 * kSlotBytes + wg * kSlotBytes + (warp & 3) * 2048;
        const uint32_t st_addr = __shfl_sync(~0u, stg + (lane & 7) * 128 + (((lane >> 3) ^ (lane & 7)) << 4), lane);
        const uint32_t ld_addr = __shfl_sync(~0u, stg + (lane >> 3) * 128 + (((lane & 7) ^ (lane >> 3)) << 4), lane);
        const uint32_t out_off = __shfl_sync(~0u, ((bh * kRows + warp * 16 + (lane >> 3)) * kD + (lane & 7) * 8) * 2, lane);
        float o[64], s[32];
        uint32_t qf[32], p[16];
#pragma unroll
        for (int i = 0; i < 16; i++) p[i] = 0;
#pragma unroll
        for (int i = 0; i < 64; i++) o[i] = 0.f;
#pragma unroll
        for (int i = 0; i < 32; i++) asm volatile("" : "=f"(s[i]));
        float m0 = -1e30f, m1 = -1e30f, n0 = -m0 * c, n1 = n0, l0 = 0.f, l1 = 0.f;
        {
            const int row = wg * 64 + (warp & 3) * 16 + (lane & 7) + ((lane >> 3) & 1) * 8;
#pragma unroll
            for (int half = 0; half < 2; half++) {
                mbar_wait(s_bar + 8 * half, 0);
                const uint32_t base = sbase + half * kSlotBytes + row * 128;
#pragma unroll
                for (int ks = 0; ks < 4; ks++) {
                    const uint32_t addr = base + (((ks * 2 + (lane >> 4)) ^ (lane & 7)) << 4);
                    uint32_t* f = qf + (half * 4 + ks) * 4;
                    asm volatile("ldmatrix.sync.aligned.m8n8.x4.shared.b16 {%0, %1, %2, %3}, [%4];"
                                 : "=r"(f[0]), "=r"(f[1]), "=r"(f[2]), "=r"(f[3]) : "r"(addr) : "memory");
                }
            }
            __syncwarp();
            mbar_arrive_if(s_bar + 16, lane == 0);
        }

        float w0, w1;
        auto exps = [&](uint32_t (&p)[16]) {
            float v0, v1;
#pragma unroll
            for (int i = 0; i < 8; i++) {
                const float e0 = ex2(fmaf(s[4 * i], c, n0)), e1 = ex2(fmaf(s[4 * i + 1], c, n0));
                const float e2 = ex2(fmaf(s[4 * i + 2], c, n1)), e3 = ex2(fmaf(s[4 * i + 3], c, n1));
                w0 = i ? w0 + e0 : e0;
                v0 = i ? v0 + e1 : e1;
                w1 = i ? w1 + e2 : e2;
                v1 = i ? v1 + e3 : e3;
                p[2 * i] = pack_bf16(e0, e1);
                p[2 * i + 1] = pack_bf16(e2, e3);
            }
            w0 += v0;
            w1 += v1;
        };
        auto must_redo = [&](int skip) { return __any_sync(~0u, fmaxf(w0, w1) > kMaxGrowth || skip > 0); };
        auto redo = [&](int skip, uint32_t (&p)[16], auto&& rescale_pending) {
            const int col = (lane & 3) * 2;
            float x0 = m0, x1 = m1;
#pragma unroll
            for (int i = 0; i < 8; i++) {
                if (i * 8 + col < skip) { s[4 * i] = -INFINITY; s[4 * i + 2] = -INFINITY; }
                if (i * 8 + col + 1 < skip) { s[4 * i + 1] = -INFINITY; s[4 * i + 3] = -INFINITY; }
                x0 = fmaxf(x0, fmaxf(s[4 * i], s[4 * i + 1]));
                x1 = fmaxf(x1, fmaxf(s[4 * i + 2], s[4 * i + 3]));
            }
            x0 = fmaxf(x0, __shfl_xor_sync(~0u, x0, 1));
            x1 = fmaxf(x1, __shfl_xor_sync(~0u, x1, 1));
            x0 = fmaxf(x0, __shfl_xor_sync(~0u, x0, 2));
            x1 = fmaxf(x1, __shfl_xor_sync(~0u, x1, 2));
            const float a0 = ex2((m0 - x0) * c), a1 = ex2((m1 - x1) * c);
            m0 = x0;
            m1 = x1;
            n0 = -x0 * c;
            n1 = -x1 * c;
            l0 *= a0;
            l1 *= a1;
#pragma unroll
            for (int i = 0; i < 16; i++) {
                o[4 * i] *= a0;
                o[4 * i + 1] *= a0;
                o[4 * i + 2] *= a1;
                o[4 * i + 3] *= a1;
                rescale_pending(i, i & 1 ? a1 : a0);
            }
            exps(p);
        };
        auto issue_qk = [&](int slot) {
            const uint32_t lo = desc_base + kLboK + slot * (2 * kSlotBytes >> 4);
#pragma unroll
            for (int ks = 0; ks < 8; ks++)
                wgmma_n64<0>(s, qf + ks * 4, lo + (ks >> 2) * 64 + (ks & 3) * 2, kDescHi, ks != 0);
        };
        auto issue_pv = [&](int slot) {
            const uint32_t lo = desc_base + kLboV + (kSlotBytes >> 4) + slot * (2 * kSlotBytes >> 4);
#pragma unroll
            for (int ks = 0; ks < 4; ks++) wgmma_pv(o, p + ks * 4, lo + ks * 256, kDescHi, 1);
        };
        auto turn_begin = [&]() {
            asm volatile("bar.sync %0, 256;" ::"r"(4 + wg) : "memory");
        };
        auto turn_end = [&]() {
            asm volatile("bar.arrive %0, 256;" ::"r"(5 - wg) : "memory");
        };

        Ring rv{0, 0}, r{1, 0};
        int skip = (top + 1) * kTileN - len;
        int t = max(top, kLead - 1);
        fence_regs(qf);
#pragma unroll 1
        do {
            const uint32_t bar_v = s_bar + 32 * rv.slot + 8, bar_k = s_bar + 32 * r.slot;
            fence_regs(s);
            fence_regs(o);
            fence_regs(p);
            mbar_wait(bar_v, rv.phase);
            turn_begin();
            wgmma_fence();
            issue_pv(rv.slot);
            wgmma_commit();
            mbar_wait(bar_k, r.phase);
            wgmma_fence();
            issue_qk(r.slot);
            wgmma_commit();
            turn_end();
            rv = r;
            r.advance();
            wgmma_wait<0>();
            fence_regs(s);
            fence_regs(o);
            fence_regs(p);
            mbar_arrive_if(bar_k + 16, lane == 0);
            mbar_arrive_if(bar_v + 16, lane == 1);
            exps(p);
            if (must_redo(skip)) redo(skip, p, [](int, float) {});
            skip = 0;
            l0 += w0;
            l1 += w1;
        } while (--t >= kLead - 1);
        auto scores = [&](int t, uint32_t (&e)[16], auto&& rescale_pending) {
            fence_regs(s);
            turn_begin();
            mbar_wait(s_bar + 32 * r.slot, r.phase);
            wgmma_fence();
            issue_qk(r.slot);
            wgmma_commit();
            turn_end();
            r.advance();
            wgmma_wait<0>();
            fence_regs(s);
            exps(e);
            if (must_redo(top <= t)) redo(top <= t ? kTileN : 0, e, rescale_pending);
            l0 += w0;
            l1 += w1;
        };
        uint32_t p2[16], p1[16], p0[16];
        scores(2, p2, [&](int i, float a) { scale_bf16(p[i], a); });
        scores(1, p1, [&](int i, float a) { scale_bf16(p[i], a); scale_bf16(p2[i], a); });
        scores(0, p0, [&](int i, float a) { scale_bf16(p[i], a); scale_bf16(p2[i], a); scale_bf16(p1[i], a); });
        fence_regs(o);
        fence_regs(p);
        fence_regs(p2);
        fence_regs(p1);
        fence_regs(p0);
        float oa[32], ob[32];
#pragma unroll
        for (int i = 0; i < 32; i++) {
            asm volatile("mov.b32 %0, %1;" : "=f"(oa[i]) : "f"(o[i]));
            asm volatile("mov.b32 %0, %1;" : "=f"(ob[i]) : "f"(o[32 + i]));
        }
        asm volatile("st.shared.v2.f32 [%0], {%1, %2};" ::"r"(stg + lane * 8), "f"(l0), "f"(l1) : "memory");
        {
            const uint32_t lo = desc_base + (kSlotBytes >> 4) + rv.slot * (2 * kSlotBytes >> 4);
            mbar_wait(s_bar + 32 * rv.slot + 8, rv.phase);
            turn_begin();
            wgmma_fence();
#pragma unroll
            for (int ks = 0; ks < 4; ks++) wgmma_n64<1>(ob, p + ks * 4, lo + 64 + ks * 256, kDescHi, 1);
#pragma unroll
            for (int ks = 0; ks < 4; ks++) wgmma_n64<1>(oa, p + ks * 4, lo + ks * 256, kDescHi, 1);
            wgmma_commit();
            turn_end();
            rv.advance();
        }
        float4 la, lb;
        asm volatile("ld.shared.v4.f32 {%0, %1, %2, %3}, [%4];" : "=f"(la.x), "=f"(la.y), "=f"(la.z), "=f"(la.w)
                     : "r"(stg + (lane >> 2) * 32) : "memory");
        asm volatile("ld.shared.v4.f32 {%0, %1, %2, %3}, [%4];" : "=f"(lb.x), "=f"(lb.y), "=f"(lb.z), "=f"(lb.w)
                     : "r"(stg + (lane >> 2) * 32 + 16) : "memory");
        float i0 = (la.x + la.z) + (lb.x + lb.z), i1 = (la.y + la.w) + (lb.y + lb.w);
        asm("rcp.approx.ftz.f32 %0, %0;" : "+f"(i0));
        asm("rcp.approx.ftz.f32 %0, %0;" : "+f"(i1));
        mbar_arrive_if(s_bar, i0 + i1 < 0.f);
        auto pv_piece = [&](int j, const uint32_t (&p)[16], float (&d)[32]) {
            const uint32_t lo = desc_base + (kSlotBytes >> 4) + rv.slot * (2 * kSlotBytes >> 4) + (j & 1) * 512;
            mbar_wait(s_bar_last + 8 * j, 0);
            wg1_sync(6 + j, wg);
            wgmma_fence();
#pragma unroll
            for (int ks = 0; ks < 4; ks++)
                wgmma_n64<1>(d, p + ks * 4, lo + ks * 128, (1024u >> 4) | (1u << 30), 1);
            wgmma_commit();
            if (j < 2 * kSplit - 1) wg0_arrive(6 + j, wg);
            if (j & 1) rv.advance();
        };
        auto stage_rows = [&](int half, int r, const float (&d)[32]) {
            const float a = r ? i1 : i0;
#pragma unroll
            for (int i = 0; i < 2; i++) {
                const float* y = d + 16 * i + 2 * r;
                asm volatile("stmatrix.sync.aligned.m8n8.x4.shared.b16 [%0], {%1, %2, %3, %4};"
                             ::"r"((st_addr ^ (64 * i)) + half * 8192 + r * 1024), "r"(pack_bf16(y[0] * a, y[1] * a)),
                             "r"(pack_bf16(y[4] * a, y[5] * a)), "r"(pack_bf16(y[8] * a, y[9] * a)),
                             "r"(pack_bf16(y[12] * a, y[13] * a)) : "memory");
            }
        };
        pv_piece(0, p2, oa);
        pv_piece(1, p1, oa);
        pv_piece(2, p0, oa);
        wgmma_wait<0>();
        fence_regs(oa);
        stage_rows(0, 0, oa);
        stage_rows(0, 1, oa);
        asm volatile("bar.arrive %0, 192;" ::"r"(2 + wg) : "memory");
        fence_regs(ob);
        pv_piece(3, p2, ob);
        pv_piece(4, p1, ob);
        pv_piece(5, p0, ob);
        wgmma_wait<0>();
        fence_regs(ob);
        char* dst = reinterpret_cast<char*>(out) + out_off;
#pragma unroll
        for (int r = 0; r < 2; r++) {
            stage_rows(1, r, ob);
            if (r == 0) wg0_arrive(5 + 2 * kSplit, wg);
            __syncwarp();
#pragma unroll
            for (int i = 2 * r; i < 2 * r + 2; i++) {
                uint4 v;
                asm volatile("ld.shared.v4.b32 {%0, %1, %2, %3}, [%4];" : "=r"(v.x), "=r"(v.y), "=r"(v.z), "=r"(v.w)
                             : "r"((ld_addr ^ (64 * (i & 1))) + i * 512 + 8192) : "memory");
                asm volatile("st.global.v4.b32 [%0], {%1, %2, %3, %4};" ::"l"(dst + i * 1024 + 128),
                             "r"(v.x), "r"(v.y), "r"(v.z), "r"(v.w) : "memory");
            }
        }
    }
}

typedef CUresult (*EncodeTiledFn)(CUtensorMap*, CUtensorMapDataType, cuuint32_t, void*, const cuuint64_t*,
                                  const cuuint64_t*, const cuuint32_t*, const cuuint32_t*, CUtensorMapInterleave,
                                  CUtensorMapSwizzle, CUtensorMapL2promotion, CUtensorMapFloatOOBfill);

}

extern "C" void kernel_launch(void* const* d_in, const int* in_sizes, int n_in, void* d_out, int out_size) {
    (void)n_in; (void)out_size;
    const int num_phys = in_sizes[1] / (kPage * kHkv * kD);

    static EncodeTiledFn encode = nullptr;
    static unsigned* progress = nullptr;
    static float tile_ns = 0.f;
    if (!encode) {
        int dev = 0, khz = 0, bits = 0;
        cudaGetDevice(&dev);
        cudaDeviceGetAttribute(&khz, cudaDevAttrMemoryClockRate, dev);
        cudaDeviceGetAttribute(&bits, cudaDevAttrGlobalMemoryBusWidth, dev);
        const float peak_gbs = 2.f * (float)khz * (float)(bits / 8) * 1e-6f;
        tile_ns = 2 * kSlotBytes / (kDramEfficiency * (peak_gbs > 0.f ? peak_gbs : 3352.f));
        cudaGetSymbolAddress((void**)&progress, g_progress);
        cudaDriverEntryPointQueryResult qr;
        cudaGetDriverEntryPoint("cuTensorMapEncodeTiled", (void**)&encode, cudaEnableDefault, &qr);
        cudaFuncSetAttribute(paged_attn_kernel, cudaFuncAttributeMaxDynamicSharedMemorySize, kSmemBytes);
    }
    Maps tm;
    auto cache_map = [&](CUtensorMap* map, void* cache, cuuint32_t halves, cuuint32_t groups) {
        const cuuint64_t dim[4] = {64, 8, 2 * kHkv, (cuuint64_t)num_phys * 2};
        const cuuint64_t str[3] = {kHkv * kD * 2, 128, 8 * kHkv * kD * 2};
        const cuuint32_t box[4] = {64, 8, halves, groups};
        const cuuint32_t es[4] = {1, 1, 1, 1};
        encode(map, CU_TENSOR_MAP_DATA_TYPE_BFLOAT16, 4, cache, dim, str, box, es, CU_TENSOR_MAP_INTERLEAVE_NONE,
               CU_TENSOR_MAP_SWIZZLE_128B, CU_TENSOR_MAP_L2_PROMOTION_L2_128B, CU_TENSOR_MAP_FLOAT_OOB_FILL_NONE);
    };
    for (int kv = 0; kv < 2; kv++) {
        cache_map(&tm.page[kv], d_in[1 + kv], 2, 2);
        cache_map(&tm.group[kv], d_in[1 + kv], 2, 1);
    }
    cache_map(&tm.vhalf, d_in[2], 1, 2);
    {
        const cuuint64_t dim[2] = {kD, (cuuint64_t)kB * kHkv * kRows};
        const cuuint64_t str[1] = {kD * 2};
        const cuuint32_t box[2] = {64, kRows};
        const cuuint32_t es[2] = {1, 1};
        encode(&tm.q, CU_TENSOR_MAP_DATA_TYPE_BFLOAT16, 2, d_in[0], dim, str, box, es, CU_TENSOR_MAP_INTERLEAVE_NONE,
               CU_TENSOR_MAP_SWIZZLE_128B, CU_TENSOR_MAP_L2_PROMOTION_L2_128B, CU_TENSOR_MAP_FLOAT_OOB_FILL_NONE);
        const cuuint32_t obox[2] = {64, 64};
        encode(&tm.out, CU_TENSOR_MAP_DATA_TYPE_BFLOAT16, 2, d_out, dim, str, obox, es, CU_TENSOR_MAP_INTERLEAVE_NONE,
               CU_TENSOR_MAP_SWIZZLE_128B, CU_TENSOR_MAP_L2_PROMOTION_NONE, CU_TENSOR_MAP_FLOAT_OOB_FILL_NONE);
    }
    paged_attn_kernel<<<kB * kHkv, kThreads, kSmemBytes>>>(
        (const int*)d_in[4], (const int*)d_in[3], (const __nv_bfloat16*)d_in[0], (__nv_bfloat16*)d_out, progress,
        num_phys * 2, tile_ns, tm);
}
```

```cpp
#include <cuda_runtime.h>
#include <cuda.h>
#include <cuda_bf16.h>
#include <stdint.h>

namespace {

constexpr int kB = 16, kHkv = 8, kD = 128, kPage = 16, kNBPS = 256;
constexpr int kRows = 128;
constexpr int kSkv = kNBPS * kPage;
constexpr int kTileN = 64;
constexpr int kSlotBytes = 16384;
constexpr int kStages = 6;
constexpr float kDramEfficiency = 0.972f;
constexpr float kWindow = 1880.f;
constexpr float kTaper = 1020.f;
constexpr float kTaperSpan = 9900.f;
constexpr float kAheadK = 85.f, kAheadV = 210.f;
constexpr float kAheadR1 = 170.f, kAheadR0 = 55.f;
constexpr float kTightR0 = 0.16f;
constexpr float kStoreLead = 660.f, kStoreStagger = 0.175f;
constexpr float kStartLag = 540.f;
constexpr float kClockGain = 0.28f;
constexpr float kClockStep = 800.f;
constexpr unsigned kClockWarmup = 200;
constexpr int kLead = 4;
constexpr int kSplit = 3;
constexpr int kEvenTiles = 5;
constexpr int kQPrefetch = 16384;
constexpr float kMaxGrowth = 4096.f;
constexpr int kThreads = 384;

constexpr int kSmemRing = kStages * 2 * kSlotBytes;
constexpr int kSortWords = 160;
constexpr int kSmemHead = 4096;
constexpr int kSmemBytes = 1024 + kSmemHead + kSmemRing;

__device__ __forceinline__ uint32_t smem_u32(const void* p) {
    return (uint32_t)__cvta_generic_to_shared(p);
}
__device__ __forceinline__ void mbar_init(uint32_t bar, uint32_t cnt) {
    asm volatile("mbarrier.init.shared::cta.b64 [%0], %1;" ::"r"(bar), "r"(cnt) : "memory");
}
__device__ __forceinline__ void mbar_expect_tx(uint32_t bar, uint32_t bytes) {
    asm volatile("mbarrier.arrive.expect_tx.shared::cta.b64 _, [%0], %1;" ::"r"(bar), "r"(bytes) : "memory");
}
__device__ __forceinline__ void mbar_arrive_if(uint32_t bar, bool pred) {
    asm volatile("{\n.reg .pred p;\nsetp.ne.u32 p, %1, 0;\n@p mbarrier.arrive.shared::cta.b64 _, [%0];\n}"
                 ::"r"(bar), "r"((uint32_t)pred) : "memory");
}
__device__ __forceinline__ void mbar_wait(uint32_t bar, uint32_t parity) {
    asm volatile(
        "{\n.reg .pred p;\n"
        "WAIT_LOOP:\n"
        "mbarrier.try_wait.parity.shared::cta.b64 p, [%0], %1;\n"
        "@p bra WAIT_DONE;\n"
        "bra WAIT_LOOP;\n"
        "WAIT_DONE:\n}" ::"r"(bar), "r"(parity) : "memory");
}
__device__ __forceinline__ void tma_page(uint32_t dst, const CUtensorMap* tm, uint32_t bar, int c2, int c3, uint64_t pol) {
    asm volatile(
        "cp.async.bulk.tensor.4d.shared::cluster.global.mbarrier::complete_tx::bytes.L2::cache_hint"
        " [%0], [%1, {%3, %3, %4, %5}], [%2], %6;"
        ::"r"(dst), "l"(tm), "r"(bar), "r"(0), "r"(c2), "r"(c3), "l"(pol) : "memory");
}
__device__ __forceinline__ void tma_group(uint32_t dst, const CUtensorMap* tm, uint32_t bar, int c1, int c2, int c3, uint64_t pol) {
    asm volatile(
        "cp.async.bulk.tensor.4d.shared::cluster.global.mbarrier::complete_tx::bytes.L2::cache_hint"
        " [%0], [%1, {%3, %4, %5, %6}], [%2], %7;"
        ::"r"(dst), "l"(tm), "r"(bar), "r"(0), "r"(c1), "r"(c2), "r"(c3), "l"(pol) : "memory");
}
__device__ __forceinline__ void tma_2d(uint32_t dst, const CUtensorMap* tm, uint32_t bar, int c0, int c1) {
    asm volatile(
        "cp.async.bulk.tensor.2d.shared::cluster.global.mbarrier::complete_tx::bytes"
        " [%0], [%1, {%3, %4}], [%2];" ::"r"(dst), "l"(tm), "r"(bar), "r"(c0), "r"(c1)
        : "memory");
}
__device__ __forceinline__ int4 ldg_v4(const int4* p) {
    int4 v;
    asm volatile("ld.global.nc.v4.b32 {%0, %1, %2, %3}, [%4];" : "=r"(v.x), "=r"(v.y), "=r"(v.z), "=r"(v.w) : "l"(p) : "memory");
    return v;
}
__device__ __forceinline__ bool elect_one() {
    uint32_t pred;
    asm volatile("{\n.reg .pred p;\nelect.sync _|p, 0xffffffff;\nselp.u32 %0, 1, 0, p;\n}" : "=r"(pred));
    return pred;
}
__device__ __forceinline__ void wg1_sync(int id, int wg) {
    asm volatile("{\n.reg .pred p;\nsetp.ne.u32 p, %1, 0;\n@p bar.sync %0, 256;\n}" ::"r"(id), "r"(wg) : "memory");
}
__device__ __forceinline__ void wg0_arrive(int id, int wg) {
    asm volatile("{\n.reg .pred p;\nsetp.eq.u32 p, %1, 0;\n@p bar.arrive %0, 256;\n}" ::"r"(id), "r"(wg) : "memory");
}
__device__ __forceinline__ void wgmma_fence() { asm volatile("wgmma.fence.sync.aligned;" ::: "memory"); }
__device__ __forceinline__ void wgmma_commit() { asm volatile("wgmma.commit_group.sync.aligned;" ::: "memory"); }
template <int N>
__device__ __forceinline__ void wgmma_wait() { asm volatile("wgmma.wait_group.sync.aligned %0;" ::"n"(N) : "memory"); }
template <int N>
__device__ __forceinline__ void fence_regs(float (&r)[N]) {
#pragma unroll
    for (int i = 0; i < N; i++) asm volatile("" : "+f"(r[i])::"memory");
}
template <int N>
__device__ __forceinline__ void fence_regs(uint32_t (&r)[N]) {
#pragma unroll
    for (int i = 0; i < N; i++) asm volatile("" : "+r"(r[i])::"memory");
}
__device__ __forceinline__ float ex2(float x) {
    float y;
    asm("ex2.approx.ftz.f32 %0, %1;" : "=f"(y) : "f"(x));
    return y;
}
__device__ __forceinline__ uint32_t pack_bf16(float lo, float hi) {
    uint32_t r;
    asm("cvt.rn.bf16x2.f32 %0, %1, %2;" : "=r"(r) : "f"(hi), "f"(lo));
    return r;
}

__device__ __forceinline__ void scale_bf16(uint32_t& p, float a) {
    p = pack_bf16(__uint_as_float(p << 16) * a, __uint_as_float(p & 0xffff0000u) * a);
}

template <int TB>
__device__ __forceinline__ void wgmma_n64(float (&d)[32], const uint32_t* a, uint32_t desc_lo, uint32_t desc_hi, int scale_d) {
    asm volatile(
        "{\n.reg .pred p;\n.reg .b64 db;\n"
        "setp.ne.b32 p, %38, 0;\n"
        "mov.b64 db, {%36, %37};\n"
        "wgmma.mma_async.sync.aligned.m64n64k16.f32.bf16.bf16 "
        "{%0, %1, %2, %3, %4, %5, %6, %7, %8, %9, %10, %11, %12, %13, %14, %15, "
        "%16, %17, %18, %19, %20, %21, %22, %23, %24, %25, %26, %27, %28, %29, %30, %31}, "
        "{%32, %33, %34, %35}, db, p, 1, 1, %39;\n}"
        : "+f"(d[0]), "+f"(d[1]), "+f"(d[2]), "+f"(d[3]), "+f"(d[4]), "+f"(d[5]), "+f"(d[6]), "+f"(d[7]),
          "+f"(d[8]), "+f"(d[9]), "+f"(d[10]), "+f"(d[11]), "+f"(d[12]), "+f"(d[13]), "+f"(d[14]), "+f"(d[15]),
          "+f"(d[16]), "+f"(d[17]), "+f"(d[18]), "+f"(d[19]), "+f"(d[20]), "+f"(d[21]), "+f"(d[22]), "+f"(d[23]),
          "+f"(d[24]), "+f"(d[25]), "+f"(d[26]), "+f"(d[27]), "+f"(d[28]), "+f"(d[29]), "+f"(d[30]), "+f"(d[31])
        : "r"(a[0]), "r"(a[1]), "r"(a[2]), "r"(a[3]), "r"(desc_lo), "r"(desc_hi), "r"(scale_d), "n"(TB));
}
__device__ __forceinline__ void wgmma_pv(float (&d)[64], const uint32_t* a, uint32_t desc_lo, uint32_t desc_hi, int scale_d) {
    asm volatile(
        "{\n.reg .pred p;\n.reg .b64 db;\n"
        "setp.ne.b32 p, %70, 0;\n"
        "mov.b64 db, {%68, %69};\n"
        "wgmma.mma_async.sync.aligned.m64n128k16.f32.bf16.bf16 "
        "{%0, %1, %2, %3, %4, %5, %6, %7, %8, %9, %10, %11, %12, %13, %14, %15, "
        "%16, %17, %18, %19, %20, %21, %22, %23, %24, %25, %26, %27, %28, %29, %30, %31, "
        "%32, %33, %34, %35, %36, %37, %38, %39, %40, %41, %42, %43, %44, %45, %46, %47, "
        "%48, %49, %50, %51, %52, %53, %54, %55, %56, %57, %58, %59, %60, %61, %62, %63}, "
        "{%64, %65, %66, %67}, db, p, 1, 1, 1;\n}"
        : "+f"(d[0]), "+f"(d[1]), "+f"(d[2]), "+f"(d[3]), "+f"(d[4]), "+f"(d[5]), "+f"(d[6]), "+f"(d[7]),
          "+f"(d[8]), "+f"(d[9]), "+f"(d[10]), "+f"(d[11]), "+f"(d[12]), "+f"(d[13]), "+f"(d[14]), "+f"(d[15]),
          "+f"(d[16]), "+f"(d[17]), "+f"(d[18]), "+f"(d[19]), "+f"(d[20]), "+f"(d[21]), "+f"(d[22]), "+f"(d[23]),
          "+f"(d[24]), "+f"(d[25]), "+f"(d[26]), "+f"(d[27]), "+f"(d[28]), "+f"(d[29]), "+f"(d[30]), "+f"(d[31]),
          "+f"(d[32]), "+f"(d[33]), "+f"(d[34]), "+f"(d[35]), "+f"(d[36]), "+f"(d[37]), "+f"(d[38]), "+f"(d[39]),
          "+f"(d[40]), "+f"(d[41]), "+f"(d[42]), "+f"(d[43]), "+f"(d[44]), "+f"(d[45]), "+f"(d[46]), "+f"(d[47]),
          "+f"(d[48]), "+f"(d[49]), "+f"(d[50]), "+f"(d[51]), "+f"(d[52]), "+f"(d[53]), "+f"(d[54]), "+f"(d[55]),
          "+f"(d[56]), "+f"(d[57]), "+f"(d[58]), "+f"(d[59]), "+f"(d[60]), "+f"(d[61]), "+f"(d[62]), "+f"(d[63])
        : "r"(a[0]), "r"(a[1]), "r"(a[2]), "r"(a[3]), "r"(desc_lo), "r"(desc_hi), "r"(scale_d));
}

__device__ __forceinline__ int bcast(int v, int lane, int src) {
    return __reduce_max_sync(~0u, lane == src ? v : 0);
}

__device__ __forceinline__ void sort_pages(const int4& row0, const int4& row1, int first, int n, int lane,
                                           uint32_t s_list, uint32_t s_bits) {
    constexpr int kW = kSortWords / 32;
    const uint32_t e[8] = {(uint32_t)row0.x, (uint32_t)row0.y, (uint32_t)row0.z, (uint32_t)row0.w,
                           (uint32_t)row1.x, (uint32_t)row1.y, (uint32_t)row1.z, (uint32_t)row1.w};
    uint32_t wa[8];
#pragma unroll
    for (int i = 0; i < 8; i++) {
        const bool use = (unsigned)(lane - first + (i >> 2) * 32) < (unsigned)n && e[i] < kSortWords * 32;
        wa[i] = s_bits + (use ? e[i] >> 5 : 0) * 8;
        asm volatile("{\n.reg .pred p;\nsetp.ne.u32 p, %2, 0;\n@p red.shared.or.b32 [%0], %1;\n}"
                     ::"r"(wa[i]), "r"(1u << (e[i] & 31)), "r"((uint32_t)use) : "memory");
    }
    __syncwarp();
    uint32_t cnt[kW + 1];
    cnt[0] = 0;
#pragma unroll
    for (int i = 0; i < kW; i++) {
        uint32_t w;
        asm volatile("ld.shared.b32 %0, [%1];" : "=r"(w) : "r"(s_bits + (lane * kW + i) * 8) : "memory");
        cnt[i + 1] = cnt[i] + __popc(w);
    }
    uint32_t scan = cnt[kW];
#pragma unroll
    for (int o = 1; o < 32; o <<= 1) {
        const uint32_t v = __shfl_up_sync(~0u, scan, o);
        if (lane >= o) scan += v;
    }
    const bool sorted = __shfl_sync(~0u, scan, 31) == (uint32_t)n * 4;
#pragma unroll
    for (int i = 0; i < kW; i++)
        asm volatile("st.shared.b32 [%0], %1;" ::"r"(s_bits + (lane * kW + i) * 8 + 4), "r"(scan - cnt[kW] + cnt[i]) : "memory");
    __syncwarp();
#pragma unroll
    for (int i = 0; i < 8; i++) {
        uint32_t w, base;
        asm volatile("ld.shared.v2.b32 {%0, %1}, [%2];" : "=r"(w), "=r"(base) : "r"(wa[i]) : "memory");
        wa[i] = base + __popc(w & ((1u << (e[i] & 31)) - 1));
    }
#pragma unroll
    for (int i = 0; i < 8; i++) {
        const uint32_t pos = sorted ? wa[i] : (lane - first) * 4 + (i >> 2) * 128 + (i & 3);
        asm volatile("{\n.reg .pred p;\nsetp.ne.u32 p, %2, 0;\n@p st.shared.b32 [%0], %1;\n}"
                     ::"r"(s_list + pos * 4), "r"(e[i] * 2), "r"((uint32_t)((unsigned)(lane - first + (i >> 2) * 32) < (unsigned)n)) : "memory");
    }
}

__device__ unsigned g_progress;

struct Maps {
    CUtensorMap page[2];
    CUtensorMap group[2];
    CUtensorMap vhalf;
    CUtensorMap q;
    CUtensorMap out;
};

struct Ring {
    int slot;
    uint32_t phase;
    __device__ __forceinline__ void advance() {
        if (++slot == kStages) { slot = 0; phase ^= 1; }
    }
};

__global__ void __launch_bounds__(kThreads, 1)
paged_attn_kernel(const int* __restrict__ ctx, const int* __restrict__ table, const __nv_bfloat16* __restrict__ q,
                  __nv_bfloat16* __restrict__ out, unsigned* progress, int oob_coord, float tile_ns,
                  const __grid_constant__ Maps tm) {
    extern __shared__ uint8_t smem_raw[];
    const int tid = threadIdx.x, lane = tid & 31;
    const int b = blockIdx.x / kHkv, h = blockIdx.x % kHkv;
    const int bh = b * kHkv + h;
    const __nv_bfloat16* q_tile = q + (size_t)bh * kRows * kD;
    if (elect_one()) asm volatile("cp.async.bulk.prefetch.L2.global [%0], %1;" ::"l"(q_tile), "r"(16) : "memory");
    if (tid == 0) asm volatile("cp.async.bulk.prefetch.L2.global [%0], %1;" ::"l"(q_tile), "r"(kQPrefetch) : "memory");
    uint32_t t_begin;
    asm volatile("mov.u32 %0, %globaltimer_lo;" : "=r"(t_begin) :: "memory");
    int cl;
    int4 row0, row1;
    if (tid >= 256) {
        const bool head = tid >> 5 == 10;
        const int4* row = reinterpret_cast<const int4*>(table + b * kNBPS) + (head ? 0 : lane);
        row0 = ldg_v4(row);
        asm volatile("ld.global.nc.b32 %0, [%1];" : "=r"(cl) : "l"(ctx + (lane & (kB - 1))) : "memory");
        row1 = ldg_v4(row + (head ? 0 : 32));
    }
    const int warp = __shfl_sync(~0u, tid >> 5, 0);
    const uint32_t sbase = __reduce_max_sync(~0u, (smem_u32(smem_raw) + 1023 + kSmemHead) & ~1023u);
    const uint32_t s_bits = sbase - 4096, s_list = sbase - 2048;
    const uint32_t s_bar = sbase - 1024, s_clock = sbase - 512;
    const uint32_t s_bar_last = s_bar + 32 * kStages;
    static_assert(kStages == 6 && kLead == 4 && kSplit == 3, "barrier layout, code of the last tiles");

    if (warp < 8) {
        if (elect_one()) {
            mbar_init(s_bar + 32 * warp, 1);
            mbar_init(s_bar + 32 * warp + 8, 1);
            mbar_init(s_bar + 32 * warp + 16, warp < kStages ? 9 : 1);
            mbar_init(s_bar + 32 * warp + 24, warp < kStages ? 8 : 1);
            asm volatile("fence.mbarrier_init.release.cluster;" ::: "memory");
            if (warp < 2 || warp >= kStages) {
                mbar_expect_tx(s_bar + 32 * warp, warp < 2 ? kSlotBytes : kSlotBytes / 2);
                mbar_expect_tx(s_bar + 32 * warp + 8, warp < 2 ? kSlotBytes : kSlotBytes / 2);
            }
            if (warp >= kStages) {
                mbar_expect_tx(s_bar + 32 * warp + 16, kSlotBytes / 2);
                mbar_expect_tx(s_bar + 32 * warp + 24, kSlotBytes / 2);
            }
            if (warp == 0) {
                asm volatile("fence.proxy.async.shared::cta;" ::: "memory");
                tma_2d(sbase, &tm.q, s_bar, 0, bh * kRows);
                tma_2d(sbase + kSlotBytes, &tm.q, s_bar + 8, 64, bh * kRows);
            }
        }
    } else if (warp == 8) {
#pragma unroll
        for (int i = 0; i < kSortWords / 32; i++)
            asm volatile("st.shared.b32 [%0], %1;" ::"r"(s_bits + (lane * (kSortWords / 32) + i) * 8), "r"(0) : "memory");
    }
    __syncthreads();

    if (warp >= 8) {
        asm volatile("setmaxnreg.dec.sync.aligned.u32 40;");
        const int kv = (warp >> 1) & 1;
        uint64_t pol;
        asm volatile("createpolicy.fractional.L2::evict_first.b64 %0, 1.0;" : "=l"(pol));
        const int len_l = cl <= 0 ? kSkv : min(cl, kSkv);
        const int len = bcast(len_l, lane, b);
        const int top = (len - 1) / kTileN;
        const int n = max(top, kLead - 1);
        const int early = top > kLead;
        if (warp == 10 && early && elect_one()) {
#pragma unroll
            for (int i = 0; i < 2; i++) {
                const uint32_t dst = sbase + (4 + i) * kSlotBytes, bar = s_bar + 64 + 8 * i;
                mbar_expect_tx(bar, kSlotBytes);
                tma_page(dst, &tm.page[i], bar, h * 2, row0.x * 2, pol);
                tma_page(dst + 4096, &tm.page[i], bar, h * 2, row0.y * 2, pol);
                tma_page(dst + 8192, &tm.page[i], bar, h * 2, row0.z * 2, pol);
                tma_page(dst + 12288, &tm.page[i], bar, h * 2, row0.w * 2, pol);
            }
        }
        if (warp & 1) {
            const int4 src = top < 32 ? row0 : row1;
            const int p0 = bcast(src.x, lane, top & 31) * 2, p1 = bcast(src.y, lane, top & 31) * 2;
            const int p2 = bcast(src.z, lane, top & 31) * 2, p3 = bcast(src.w, lane, top & 31) * 2;
            const int rem = len - top * kTileN, full = (rem - 1) / kPage, r = rem - full * kPage;
            const int last = full == 0 ? p0 : full == 1 ? p1 : full == 2 ? p2 : p3;
            const uint32_t off = (3 - full) * 4096;
            if (elect_one()) {
                const uint32_t dst = sbase + (2 + kv) * kSlotBytes, bar = s_bar + 32 + 8 * kv;
                tma_page(dst + ((off + 4096) & 0x3fff), &tm.page[kv], bar, h * 2, full > 0 ? p0 : oob_coord, pol);
                tma_page(dst + ((off + 8192) & 0x3fff), &tm.page[kv], bar, h * 2, full > 1 ? p1 : oob_coord, pol);
                tma_page(dst + ((off + 12288) & 0x3fff), &tm.page[kv], bar, h * 2, full > 2 ? p2 : oob_coord, pol);
                tma_group(dst + off, &tm.group[kv], bar, r - 16, h * 2, last + 1, pol);
                tma_group(dst + off + 2048, &tm.group[kv], bar, min(r - 8, 0), h * 2, last, pol);
                asm volatile("prefetch.tensormap [%0];" ::"l"(kv ? &tm.vhalf : &tm.out) : "memory");
            }
            {
                __syncwarp();
                asm volatile("bar.sync %0, 192;" ::"r"(2 + kv) : "memory");
                asm volatile("fence.proxy.async.shared::cta;" ::: "memory");
                if (elect_one()) {
                    asm volatile("cp.async.bulk.tensor.2d.global.shared::cta.bulk_group [%0, {%1, %2}], [%3];"
                                 ::"l"(&tm.out), "r"(0), "r"(bh * kRows + kv * 64),
                                 "r"(sbase + ((n + 3) % kStages * 2 + kv) * kSlotBytes) : "memory");
                    asm volatile("cp.async.bulk.commit_group;" ::: "memory");
                }
            }
            asm volatile("cp.async.bulk.wait_group.read 0;" ::: "memory");
            return;
        }
        const int full_l = lane < kB ? (len_l - 1) / kTileN : 0;
        const float t_all = (float)(__reduce_add_sync(~0u, full_l) * kHkv) * tile_ns;
        float origin = (kB * kHkv + __reduce_add_sync(~0u, lane < kB ? len_l - full_l * kTileN : 0) * (1.f / 8)) * tile_ns + kStartLag;
        if (warp == 10) {
            if (lane == 0) {
                const float gain = fminf(__fdividef(kClockGain * t_all, (float)(n * kB * kHkv) * tile_ns), 0.5f);
                mbar_arrive_if(s_bar + 16, true);
                mbar_arrive_if(s_bar + 48, true);
                Ring m{2, 0};
                unsigned g;
#pragma unroll 1
                for (int t = n - 1; t >= kLead - 2; t--) {
                    if (t == kLead - 2) m.advance();
                    mbar_wait(s_bar + 32 * m.slot, m.phase);
                    mbar_arrive_if(s_bar + 32 * m.slot + 16, true);
                    m.advance();
                    uint32_t now;
                    asm volatile("mov.u32 %0, %globaltimer_lo;" : "=r"(now) :: "memory");
                    asm volatile("atom.relaxed.gpu.global.add.u32 %0, [%1], 1;" : "=r"(g) : "l"(progress) : "memory");
                    g &= 0xfffff;
                    const float d = (float)(int)(now - t_begin) - (float)g * tile_ns - origin;
                    if (g >= kClockWarmup) origin = fmaf(fminf(d, kClockStep), gain, origin);
                    asm volatile("st.volatile.shared.b32 [%0], %1;" ::"r"(s_clock), "r"(t_begin + (int)origin) : "memory");
                }
                asm volatile("atom.relaxed.gpu.global.add.u32 %0, [%1], 0x100000;" : "=r"(g) : "l"(progress) : "memory");
                if ((g >> 20) == kB * kHkv - 1) asm volatile("st.relaxed.gpu.global.u32 [%0], 0;" ::"l"(progress) : "memory");
            }
            return;
        }
        asm volatile("st.volatile.shared.b32 [%0], %1;" ::"r"(s_clock), "r"(t_begin + (int)origin) : "memory");
        if (lane < 4 * (kLead - 1)) asm volatile("st.shared.b32 [%0], %1;" ::"r"(s_list + lane * 4), "r"(oob_coord) : "memory");
        sort_pages(row0, row1, early, top - early, lane, s_list, s_bits);
        __syncwarp();
        auto pages = [&](int t) {
            int4 pg;
            asm volatile("ld.shared.v4.b32 {%0, %1, %2, %3}, [%4];" : "=r"(pg.x), "=r"(pg.y), "=r"(pg.z), "=r"(pg.w)
                         : "r"(s_list + t * 16) : "memory");
            return pg;
        };
        const float dt_end = tile_ns * (kB * kHkv / 2);
        const float stagger = dt_end * ((b * 7 % kB) + 0.5f) * (1.f / kB);
        const float dt = __fdividef(t_all - dt_end * (2 * kEvenTiles), (float)(2 * max(n - kEvenTiles, 1)));
        float left = (n > kEvenTiles ? t_all : dt_end * (float)(2 * n)) - stagger;
        auto wait_due = [&](float step, float ahead = 0.f) {
            const int due = (int)(t_all - kWindow - left + fmaxf(fmaf(left, -kTaper / kTaperSpan, kTaper), 0.f) - ahead);
            left -= step;
#pragma unroll 1
            while (true) {
                uint32_t now, org;
                asm volatile("ld.volatile.shared.b32 %0, [%1];" : "=r"(org) : "r"(s_clock) : "memory");
                asm volatile("mov.u32 %0, %globaltimer_lo;" : "=r"(now));
                const int wait = due - (int)(now - org);
                if (wait <= 0) break;
                if (wait > 64) __nanosleep(min(wait >> 1, 200));
            }
        };
        auto acquire = [&](const Ring& r, int kv, float step, float ahead = 0.f) {
            const uint32_t bar = s_bar + 32 * r.slot + 8 * kv;
            mbar_wait(bar + 16, r.phase ^ 1);
            if (lane == 0) mbar_expect_tx(bar, kSlotBytes);
            wait_due(step, ahead);
            return bar;
        };
        auto load4 = [&](uint32_t dst, uint32_t stride, const CUtensorMap* map, uint32_t bar, int c2, const int4& pg) {
            if (elect_one()) {
                tma_page(dst, map, bar, c2, pg.x, pol);
                tma_page(dst + stride, map, bar, c2, pg.y, pol);
                tma_page(dst + 2 * stride, map, bar, c2, pg.z, pol);
                tma_page(dst + 3 * stride, map, bar, c2, pg.w, pol);
            }
        };
        Ring r{2 + early, 0};
        if (early) left -= 2.f * (n > kEvenTiles ? dt : dt_end);
#pragma unroll 1
        for (int t = n - 1 - early; t >= kLead; t--) {
            const int4 pg = pages(t);
            const uint32_t dst = sbase + 2 * r.slot * kSlotBytes;
            const float step = t < kEvenTiles ? dt_end : dt;
            load4(dst, 4096, &tm.page[0], acquire(r, 0, step), h * 2, pg);
            load4(dst + kSlotBytes, 4096, &tm.page[1], acquire(r, 1, step), h * 2, pg);
            r.advance();
        }
        Ring rv = r;
#pragma unroll 1
        for (int i = 0; i < 2 * kLead - kSplit; i++) {
            const int kv = i >= kLead;
            const int t = (kv ? 2 * kLead : kLead) - 1 - i;
            if (t >= n) continue;
            const int4 pg = pages(t);
            const Ring cur = kv ? rv : r;
            load4(sbase + (2 * cur.slot + kv) * kSlotBytes, 4096, &tm.page[kv],
                  acquire(cur, kv, dt_end, kv ? kAheadV : i ? kAheadK : 0.f), h * 2, pg);
            if (kv) rv.advance(); else r.advance();
        }
        left += 0.5f * stagger;
#pragma unroll 1
        for (int j = 0; j < 2 * kSplit; j++) {
            const int half = j >= kSplit, t = (half ? 2 * kSplit : kSplit) - 1 - j;
            const int4 pg = pages(t);
            mbar_wait(s_bar + 32 * rv.slot + 24, rv.phase ^ 1);
            wait_due(0.5f * dt_end, !half || t > 1 ? kAheadV : t ? kAheadR1 : fmaf(stagger, kTightR0, kAheadR0));
            load4(sbase + (2 * rv.slot + 1) * kSlotBytes + (j & 1) * 8192, 2048, &tm.vhalf, s_bar_last + 8 * j, h * 2 + half, pg);
            if (j & 1) rv.advance();
        }
        uint32_t due, now, landed;
        asm volatile("ld.volatile.shared.b32 %0, [%1];" : "=r"(due) : "r"(s_clock) : "memory");
        due += (int)(t_all - kStoreLead + kStoreStagger * stagger);
#pragma unroll 1
        do {
            asm volatile("{\n.reg .pred p;\nmbarrier.test_wait.parity.shared::cta.b64 p, [%1], 0;\nselp.u32 %0, 1, 0, p;\n}"
                         : "=r"(landed) : "r"(s_bar_last + 8 * (2 * kSplit - 2)) : "memory");
            asm volatile("mov.u32 %0, %globaltimer_lo;" : "=r"(now));
        } while (!landed && (int)(due - now) > 0);
        __syncwarp();
        asm volatile("bar.arrive 2, 192;" ::: "memory");
        asm volatile("bar.arrive 3, 192;" ::: "memory");
    } else {
        asm volatile("setmaxnreg.inc.sync.aligned.u32 232;");
        const int wg = warp >> 2;
        const int clb = __reduce_max_sync(~0u, __ldg(ctx + b));
        const int len = clb <= 0 ? kSkv : min(clb, kSkv);
        const int top = (len - 1) / kTileN;
        const float c = clb <= 0 ? 0.f : 0.08838834764831845f * 1.4426950408889634f;

        if (wg == 1) asm volatile("bar.arrive 4, 256;" ::: "memory");
        constexpr uint32_t kDescHi = (2048u >> 4) | (1u << 30);
        constexpr uint32_t kLboK = 1u << 16, kLboV = (1024u >> 4) << 16;
        const uint32_t desc_base = (sbase & 0x3FFFF) >> 4;

        const uint32_t stg = sbase + (max(top, kLead - 1) + 3) % kStages * 2 * kSlotBytes + wg * kSlotBytes + (warp & 3) * 2048;
        const uint32_t st_addr = __shfl_sync(~0u, stg + (lane & 7) * 128 + (((lane >> 3) ^ (lane & 7)) << 4), lane);
        const uint32_t ld_addr = __shfl_sync(~0u, stg + (lane >> 3) * 128 + (((lane & 7) ^ (lane >> 3)) << 4), lane);
        const uint32_t out_off = __shfl_sync(~0u, ((bh * kRows + warp * 16 + (lane >> 3)) * kD + (lane & 7) * 8) * 2, lane);
        float o[64], s[32];
        uint32_t qf[32], p[16];
#pragma unroll
        for (int i = 0; i < 16; i++) p[i] = 0;
#pragma unroll
        for (int i = 0; i < 64; i++) o[i] = 0.f;
#pragma unroll
        for (int i = 0; i < 32; i++) asm volatile("" : "=f"(s[i]));
        float m0 = -1e30f, m1 = -1e30f, n0 = -m0 * c, n1 = n0, l0 = 0.f, l1 = 0.f;
        {
            const int row = wg * 64 + (warp & 3) * 16 + (lane & 7) + ((lane >> 3) & 1) * 8;
#pragma unroll
            for (int half = 0; half < 2; half++) {
                mbar_wait(s_bar + 8 * half, 0);
                const uint32_t base = sbase + half * kSlotBytes + row * 128;
#pragma unroll
                for (int ks = 0; ks < 4; ks++) {
                    const uint32_t addr = base + (((ks * 2 + (lane >> 4)) ^ (lane & 7)) << 4);
                    uint32_t* f = qf + (half * 4 + ks) * 4;
                    asm volatile("ldmatrix.sync.aligned.m8n8.x4.shared.b16 {%0, %1, %2, %3}, [%4];"
                                 : "=r"(f[0]), "=r"(f[1]), "=r"(f[2]), "=r"(f[3]) : "r"(addr) : "memory");
                }
            }
            __syncwarp();
            mbar_arrive_if(s_bar + 16, lane == 0);
        }

        float w0, w1;
        auto exps = [&](uint32_t (&p)[16]) {
            float v0, v1;
#pragma unroll
            for (int i = 0; i < 8; i++) {
                const float e0 = ex2(fmaf(s[4 * i], c, n0)), e1 = ex2(fmaf(s[4 * i + 1], c, n0));
                const float e2 = ex2(fmaf(s[4 * i + 2], c, n1)), e3 = ex2(fmaf(s[4 * i + 3], c, n1));
                w0 = i ? w0 + e0 : e0;
                v0 = i ? v0 + e1 : e1;
                w1 = i ? w1 + e2 : e2;
                v1 = i ? v1 + e3 : e3;
                p[2 * i] = pack_bf16(e0, e1);
                p[2 * i + 1] = pack_bf16(e2, e3);
            }
            w0 += v0;
            w1 += v1;
        };
        auto must_redo = [&](int skip) { return __any_sync(~0u, fmaxf(w0, w1) > kMaxGrowth || skip > 0); };
        auto redo = [&](int skip, uint32_t (&p)[16], auto&& rescale_pending) {
            const int col = (lane & 3) * 2;
            float x0 = m0, x1 = m1;
#pragma unroll
            for (int i = 0; i < 8; i++) {
                if (i * 8 + col < skip) { s[4 * i] = -INFINITY; s[4 * i + 2] = -INFINITY; }
                if (i * 8 + col + 1 < skip) { s[4 * i + 1] = -INFINITY; s[4 * i + 3] = -INFINITY; }
                x0 = fmaxf(x0, fmaxf(s[4 * i], s[4 * i + 1]));
                x1 = fmaxf(x1, fmaxf(s[4 * i + 2], s[4 * i + 3]));
            }
            x0 = fmaxf(x0, __shfl_xor_sync(~0u, x0, 1));
            x1 = fmaxf(x1, __shfl_xor_sync(~0u, x1, 1));
            x0 = fmaxf(x0, __shfl_xor_sync(~0u, x0, 2));
            x1 = fmaxf(x1, __shfl_xor_sync(~0u, x1, 2));
            const float a0 = ex2((m0 - x0) * c), a1 = ex2((m1 - x1) * c);
            m0 = x0;
            m1 = x1;
            n0 = -x0 * c;
            n1 = -x1 * c;
            l0 *= a0;
            l1 *= a1;
#pragma unroll
            for (int i = 0; i < 16; i++) {
                o[4 * i] *= a0;
                o[4 * i + 1] *= a0;
                o[4 * i + 2] *= a1;
                o[4 * i + 3] *= a1;
                rescale_pending(i, i & 1 ? a1 : a0);
            }
            exps(p);
        };
        auto issue_qk = [&](int slot) {
            const uint32_t lo = desc_base + kLboK + slot * (2 * kSlotBytes >> 4);
#pragma unroll
            for (int ks = 0; ks < 8; ks++)
                wgmma_n64<0>(s, qf + ks * 4, lo + (ks >> 2) * 64 + (ks & 3) * 2, kDescHi, ks != 0);
        };
        auto issue_pv = [&](int slot) {
            const uint32_t lo = desc_base + kLboV + (kSlotBytes >> 4) + slot * (2 * kSlotBytes >> 4);
#pragma unroll
            for (int ks = 0; ks < 4; ks++) wgmma_pv(o, p + ks * 4, lo + ks * 256, kDescHi, 1);
        };
        auto turn_begin = [&]() {
            asm volatile("bar.sync %0, 256;" ::"r"(4 + wg) : "memory");
        };
        auto turn_end = [&]() {
            asm volatile("bar.arrive %0, 256;" ::"r"(5 - wg) : "memory");
        };

        Ring rv{0, 0}, r{1, 0};
        int skip = (top + 1) * kTileN - len;
        int t = max(top, kLead - 1);
        fence_regs(qf);
#pragma unroll 1
        do {
            const uint32_t bar_v = s_bar + 32 * rv.slot + 8, bar_k = s_bar + 32 * r.slot;
            fence_regs(s);
            fence_regs(o);
            fence_regs(p);
            mbar_wait(bar_v, rv.phase);
            turn_begin();
            wgmma_fence();
            issue_pv(rv.slot);
            wgmma_commit();
            mbar_wait(bar_k, r.phase);
            wgmma_fence();
            issue_qk(r.slot);
            wgmma_commit();
            turn_end();
            rv = r;
            r.advance();
            wgmma_wait<0>();
            fence_regs(s);
            fence_regs(o);
            fence_regs(p);
            mbar_arrive_if(bar_k + 16, lane == 0);
            mbar_arrive_if(bar_v + 16, lane == 1);
            exps(p);
            if (must_redo(skip)) redo(skip, p, [](int, float) {});
            skip = 0;
            l0 += w0;
            l1 += w1;
        } while (--t >= kLead - 1);
        auto scores = [&](int t, uint32_t (&e)[16], auto&& rescale_pending) {
            fence_regs(s);
            turn_begin();
            mbar_wait(s_bar + 32 * r.slot, r.phase);
            wgmma_fence();
            issue_qk(r.slot);
            wgmma_commit();
            turn_end();
            r.advance();
            wgmma_wait<0>();
            fence_regs(s);
            exps(e);
            if (must_redo(top <= t)) redo(top <= t ? kTileN : 0, e, rescale_pending);
            l0 += w0;
            l1 += w1;
        };
        uint32_t p2[16], p1[16], p0[16];
        scores(2, p2, [&](int i, float a) { scale_bf16(p[i], a); });
        scores(1, p1, [&](int i, float a) { scale_bf16(p[i], a); scale_bf16(p2[i], a); });
        scores(0, p0, [&](int i, float a) { scale_bf16(p[i], a); scale_bf16(p2[i], a); scale_bf16(p1[i], a); });
        fence_regs(o);
        fence_regs(p);
        fence_regs(p2);
        fence_regs(p1);
        fence_regs(p0);
        float oa[32], ob[32];
#pragma unroll
        for (int i = 0; i < 32; i++) {
            asm volatile("mov.b32 %0, %1;" : "=f"(oa[i]) : "f"(o[i]));
            asm volatile("mov.b32 %0, %1;" : "=f"(ob[i]) : "f"(o[32 + i]));
        }
        asm volatile("st.shared.v2.f32 [%0], {%1, %2};" ::"r"(stg + lane * 8), "f"(l0), "f"(l1) : "memory");
        {
            const uint32_t lo = desc_base + (kSlotBytes >> 4) + rv.slot * (2 * kSlotBytes >> 4);
            mbar_wait(s_bar + 32 * rv.slot + 8, rv.phase);
            turn_begin();
            wgmma_fence();
#pragma unroll
            for (int ks = 0; ks < 4; ks++) wgmma_n64<1>(ob, p + ks * 4, lo + 64 + ks * 256, kDescHi, 1);
#pragma unroll
            for (int ks = 0; ks < 4; ks++) wgmma_n64<1>(oa, p + ks * 4, lo + ks * 256, kDescHi, 1);
            wgmma_commit();
            turn_end();
            rv.advance();
        }
        float4 la, lb;
        asm volatile("ld.shared.v4.f32 {%0, %1, %2, %3}, [%4];" : "=f"(la.x), "=f"(la.y), "=f"(la.z), "=f"(la.w)
                     : "r"(stg + (lane >> 2) * 32) : "memory");
        asm volatile("ld.shared.v4.f32 {%0, %1, %2, %3}, [%4];" : "=f"(lb.x), "=f"(lb.y), "=f"(lb.z), "=f"(lb.w)
                     : "r"(stg + (lane >> 2) * 32 + 16) : "memory");
        float i0 = (la.x + la.z) + (lb.x + lb.z), i1 = (la.y + la.w) + (lb.y + lb.w);
        asm("rcp.approx.ftz.f32 %0, %0;" : "+f"(i0));
        asm("rcp.approx.ftz.f32 %0, %0;" : "+f"(i1));
        mbar_arrive_if(s_bar, i0 + i1 < 0.f);
        uint32_t go_on = 0;
        auto pv_piece = [&](int j, const uint32_t (&p)[16], float (&d)[32]) {
            const uint32_t lo = desc_base + (kSlotBytes >> 4) + rv.slot * (2 * kSlotBytes >> 4) + (j & 1) * 512;
            mbar_wait(s_bar_last + 8 * j, 0);
            wg1_sync(6 + j, wg);
            wgmma_fence();
#pragma unroll
            for (int ks = 0; ks < 4; ks++)
                wgmma_n64<1>(d, p + ks * 4, lo + ks * 128, (1024u >> 4) | (1u << 30), 1);
            wgmma_commit();
            if (j == 2 * kSplit - 2)
                asm volatile("{\n.reg .pred p;\nmbarrier.test_wait.parity.shared::cta.b64 p, [%1], 0;\nselp.u32 %0, 1, 0, p;\n}"
                             : "=r"(go_on) : "r"(s_bar_last + 8 * j + 8) : "memory");
            if (j < 2 * kSplit - 1) wg0_arrive(6 + j, wg | go_on);
            else wg0_arrive(5 + j, wg | (go_on ^ 1));
            if (j & 1) rv.advance();
        };
        auto stage_rows = [&](int half, int r, const float (&d)[32]) {
            const float a = r ? i1 : i0;
#pragma unroll
            for (int i = 0; i < 2; i++) {
                const float* y = d + 16 * i + 2 * r;
                asm volatile("stmatrix.sync.aligned.m8n8.x4.shared.b16 [%0], {%1, %2, %3, %4};"
                             ::"r"((st_addr ^ (64 * i)) + half * 8192 + r * 1024), "r"(pack_bf16(y[0] * a, y[1] * a)),
                             "r"(pack_bf16(y[4] * a, y[5] * a)), "r"(pack_bf16(y[8] * a, y[9] * a)),
                             "r"(pack_bf16(y[12] * a, y[13] * a)) : "memory");
            }
        };
        pv_piece(0, p2, oa);
        pv_piece(1, p1, oa);
        pv_piece(2, p0, oa);
        wgmma_wait<0>();
        fence_regs(oa);
        stage_rows(0, 0, oa);
        stage_rows(0, 1, oa);
        asm volatile("bar.arrive %0, 192;" ::"r"(2 + wg) : "memory");
        fence_regs(ob);
        pv_piece(3, p2, ob);
        pv_piece(4, p1, ob);
        pv_piece(5, p0, ob);
        wgmma_wait<0>();
        fence_regs(ob);
        char* dst = reinterpret_cast<char*>(out) + out_off;
#pragma unroll
        for (int r = 0; r < 2; r++) {
            stage_rows(1, r, ob);
            if (r == 0) wg0_arrive(5 + 2 * kSplit, wg);
            __syncwarp();
#pragma unroll
            for (int i = 2 * r; i < 2 * r + 2; i++) {
                uint4 v;
                asm volatile("ld.shared.v4.b32 {%0, %1, %2, %3}, [%4];" : "=r"(v.x), "=r"(v.y), "=r"(v.z), "=r"(v.w)
                             : "r"((ld_addr ^ (64 * (i & 1))) + i * 512 + 8192) : "memory");
                asm volatile("st.global.v4.b32 [%0], {%1, %2, %3, %4};" ::"l"(dst + i * 1024 + 128),
                             "r"(v.x), "r"(v.y), "r"(v.z), "r"(v.w) : "memory");
            }
        }
    }
}

typedef CUresult (*EncodeTiledFn)(CUtensorMap*, CUtensorMapDataType, cuuint32_t, void*, const cuuint64_t*,
                                  const cuuint64_t*, const cuuint32_t*, const cuuint32_t*, CUtensorMapInterleave,
                                  CUtensorMapSwizzle, CUtensorMapL2promotion, CUtensorMapFloatOOBfill);

}

extern "C" void kernel_launch(void* const* d_in, const int* in_sizes, int n_in, void* d_out, int out_size) {
    (void)n_in; (void)out_size;
    const int num_phys = in_sizes[1] / (kPage * kHkv * kD);

    static EncodeTiledFn encode = nullptr;
    static unsigned* progress = nullptr;
    static float tile_ns = 0.f;
    if (!encode) {
        int dev = 0, khz = 0, bits = 0;
        cudaGetDevice(&dev);
        cudaDeviceGetAttribute(&khz, cudaDevAttrMemoryClockRate, dev);
        cudaDeviceGetAttribute(&bits, cudaDevAttrGlobalMemoryBusWidth, dev);
        const float peak_gbs = 2.f * (float)khz * (float)(bits / 8) * 1e-6f;
        tile_ns = 2 * kSlotBytes / (kDramEfficiency * (peak_gbs > 0.f ? peak_gbs : 3352.f));
        cudaGetSymbolAddress((void**)&progress, g_progress);
        cudaDriverEntryPointQueryResult qr;
        cudaGetDriverEntryPoint("cuTensorMapEncodeTiled", (void**)&encode, cudaEnableDefault, &qr);
        cudaFuncSetAttribute(paged_attn_kernel, cudaFuncAttributeMaxDynamicSharedMemorySize, kSmemBytes);
    }
    Maps tm;
    auto cache_map = [&](CUtensorMap* map, void* cache, cuuint32_t halves, cuuint32_t groups) {
        const cuuint64_t dim[4] = {64, 8, 2 * kHkv, (cuuint64_t)num_phys * 2};
        const cuuint64_t str[3] = {kHkv * kD * 2, 128, 8 * kHkv * kD * 2};
        const cuuint32_t box[4] = {64, 8, halves, groups};
        const cuuint32_t es[4] = {1, 1, 1, 1};
        encode(map, CU_TENSOR_MAP_DATA_TYPE_BFLOAT16, 4, cache, dim, str, box, es, CU_TENSOR_MAP_INTERLEAVE_NONE,
               CU_TENSOR_MAP_SWIZZLE_128B, CU_TENSOR_MAP_L2_PROMOTION_L2_128B, CU_TENSOR_MAP_FLOAT_OOB_FILL_NONE);
    };
    for (int kv = 0; kv < 2; kv++) {
        cache_map(&tm.page[kv], d_in[1 + kv], 2, 2);
        cache_map(&tm.group[kv], d_in[1 + kv], 2, 1);
    }
    cache_map(&tm.vhalf, d_in[2], 1, 2);
    {
        const cuuint64_t dim[2] = {kD, (cuuint64_t)kB * kHkv * kRows};
        const cuuint64_t str[1] = {kD * 2};
        const cuuint32_t box[2] = {64, kRows};
        const cuuint32_t es[2] = {1, 1};
        encode(&tm.q, CU_TENSOR_MAP_DATA_TYPE_BFLOAT16, 2, d_in[0], dim, str, box, es, CU_TENSOR_MAP_INTERLEAVE_NONE,
               CU_TENSOR_MAP_SWIZZLE_128B, CU_TENSOR_MAP_L2_PROMOTION_L2_128B, CU_TENSOR_MAP_FLOAT_OOB_FILL_NONE);
        const cuuint32_t obox[2] = {64, 64};
        encode(&tm.out, CU_TENSOR_MAP_DATA_TYPE_BFLOAT16, 2, d_out, dim, str, obox, es, CU_TENSOR_MAP_INTERLEAVE_NONE,
               CU_TENSOR_MAP_SWIZZLE_128B, CU_TENSOR_MAP_L2_PROMOTION_NONE, CU_TENSOR_MAP_FLOAT_OOB_FILL_NONE);
    }
    paged_attn_kernel<<<kB * kHkv, kThreads, kSmemBytes>>>(
        (const int*)d_in[4], (const int*)d_in[3], (const __nv_bfloat16*)d_in[0], (__nv_bfloat16*)d_out, progress,
        num_phys * 2, tile_ns, tm);
}
```

```cpp
#include <cuda_runtime.h>
#include <cuda.h>
#include <cuda_bf16.h>
#include <stdint.h>

namespace {

constexpr int kB = 16, kHkv = 8, kD = 128, kPage = 16, kNBPS = 256;
constexpr int kRows = 128;
constexpr int kSkv = kNBPS * kPage;
constexpr int kTileN = 64;
constexpr int kSlotBytes = 16384;
constexpr int kStages = 6;
constexpr float kDramEfficiency = 0.972f;
constexpr float kWindow = 1880.f;
constexpr float kTaper = 1020.f;
constexpr float kTaperSpan = 9900.f;
constexpr float kAheadK = 85.f, kAheadV = 210.f;
constexpr float kAheadR1 = 170.f, kAheadR0 = 55.f;
constexpr float kTightR0 = 0.16f;
constexpr float kStoreLead = 660.f, kStoreStagger = 0.175f;
constexpr float kStartLag = 540.f;
constexpr float kClockGain = 0.28f;
constexpr float kClockStep = 800.f;
constexpr unsigned kClockWarmup = 200;
constexpr int kLead = 4;
constexpr int kSplit = 3;
constexpr int kEvenTiles = 5;
constexpr int kQPrefetch = 16384;
constexpr float kMaxGrowth = 4096.f;
constexpr int kThreads = 384;

constexpr int kSmemRing = kStages * 2 * kSlotBytes;
constexpr int kSortWords = 160;
constexpr int kSmemHead = 4096;
constexpr int kSmemBytes = 1024 + kSmemHead + kSmemRing;

__device__ __forceinline__ uint32_t smem_u32(const void* p) {
    return (uint32_t)__cvta_generic_to_shared(p);
}
__device__ __forceinline__ void mbar_init(uint32_t bar, uint32_t cnt) {
    asm volatile("mbarrier.init.shared::cta.b64 [%0], %1;" ::"r"(bar), "r"(cnt) : "memory");
}
__device__ __forceinline__ void mbar_expect_tx(uint32_t bar, uint32_t bytes) {
    asm volatile("mbarrier.arrive.expect_tx.shared::cta.b64 _, [%0], %1;" ::"r"(bar), "r"(bytes) : "memory");
}
__device__ __forceinline__ void mbar_arrive_if(uint32_t bar, bool pred) {
    asm volatile("{\n.reg .pred p;\nsetp.ne.u32 p, %1, 0;\n@p mbarrier.arrive.shared::cta.b64 _, [%0];\n}"
                 ::"r"(bar), "r"((uint32_t)pred) : "memory");
}
__device__ __forceinline__ void mbar_wait(uint32_t bar, uint32_t parity) {
    asm volatile(
        "{\n.reg .pred p;\n"
        "WAIT_LOOP:\n"
        "mbarrier.try_wait.parity.shared::cta.b64 p, [%0], %1;\n"
        "@p bra WAIT_DONE;\n"
        "bra WAIT_LOOP;\n"
        "WAIT_DONE:\n}" ::"r"(bar), "r"(parity) : "memory");
}
__device__ __forceinline__ void tma_page(uint32_t dst, const CUtensorMap* tm, uint32_t bar, int c2, int c3, uint64_t pol) {
    asm volatile(
        "cp.async.bulk.tensor.4d.shared::cluster.global.mbarrier::complete_tx::bytes.L2::cache_hint"
        " [%0], [%1, {%3, %3, %4, %5}], [%2], %6;"
        ::"r"(dst), "l"(tm), "r"(bar), "r"(0), "r"(c2), "r"(c3), "l"(pol) : "memory");
}
__device__ __forceinline__ void tma_group(uint32_t dst, const CUtensorMap* tm, uint32_t bar, int c1, int c2, int c3, uint64_t pol) {
    asm volatile(
        "cp.async.bulk.tensor.4d.shared::cluster.global.mbarrier::complete_tx::bytes.L2::cache_hint"
        " [%0], [%1, {%3, %4, %5, %6}], [%2], %7;"
        ::"r"(dst), "l"(tm), "r"(bar), "r"(0), "r"(c1), "r"(c2), "r"(c3), "l"(pol) : "memory");
}
__device__ __forceinline__ void tma_2d(uint32_t dst, const CUtensorMap* tm, uint32_t bar, int c0, int c1) {
    asm volatile(
        "cp.async.bulk.tensor.2d.shared::cluster.global.mbarrier::complete_tx::bytes"
        " [%0], [%1, {%3, %4}], [%2];" ::"r"(dst), "l"(tm), "r"(bar), "r"(c0), "r"(c1)
        : "memory");
}
__device__ __forceinline__ int4 ldg_v4(const int4* p) {
    int4 v;
    asm volatile("ld.global.nc.v4.b32 {%0, %1, %2, %3}, [%4];" : "=r"(v.x), "=r"(v.y), "=r"(v.z), "=r"(v.w) : "l"(p) : "memory");
    return v;
}
__device__ __forceinline__ bool elect_one() {
    uint32_t pred;
    asm volatile("{\n.reg .pred p;\nelect.sync _|p, 0xffffffff;\nselp.u32 %0, 1, 0, p;\n}" : "=r"(pred));
    return pred;
}
__device__ __forceinline__ void wg1_sync(int id, int wg) {
    asm volatile("{\n.reg .pred p;\nsetp.ne.u32 p, %1, 0;\n@p bar.sync %0, 256;\n}" ::"r"(id), "r"(wg) : "memory");
}
__device__ __forceinline__ void wg0_arrive(int id, int wg) {
    asm volatile("{\n.reg .pred p;\nsetp.eq.u32 p, %1, 0;\n@p bar.arrive %0, 256;\n}" ::"r"(id), "r"(wg) : "memory");
}
__device__ __forceinline__ void wgmma_fence() { asm volatile("wgmma.fence.sync.aligned;" ::: "memory"); }
__device__ __forceinline__ void wgmma_commit() { asm volatile("wgmma.commit_group.sync.aligned;" ::: "memory"); }
template <int N>
__device__ __forceinline__ void wgmma_wait() { asm volatile("wgmma.wait_group.sync.aligned %0;" ::"n"(N) : "memory"); }
template <int N>
__device__ __forceinline__ void fence_regs(float (&r)[N]) {
#pragma unroll
    for (int i = 0; i < N; i++) asm volatile("" : "+f"(r[i])::"memory");
}
template <int N>
__device__ __forceinline__ void fence_regs(uint32_t (&r)[N]) {
#pragma unroll
    for (int i = 0; i < N; i++) asm volatile("" : "+r"(r[i])::"memory");
}
__device__ __forceinline__ float ex2(float x) {
    float y;
    asm("ex2.approx.ftz.f32 %0, %1;" : "=f"(y) : "f"(x));
    return y;
}
__device__ __forceinline__ uint32_t pack_bf16(float lo, float hi) {
    uint32_t r;
    asm("cvt.rn.bf16x2.f32 %0, %1, %2;" : "=r"(r) : "f"(hi), "f"(lo));
    return r;
}

__device__ __forceinline__ void scale_bf16(uint32_t& p, float a) {
    p = pack_bf16(__uint_as_float(p << 16) * a, __uint_as_float(p & 0xffff0000u) * a);
}

template <int TB>
__device__ __forceinline__ void wgmma_n64(float (&d)[32], const uint32_t* a, uint32_t desc_lo, uint32_t desc_hi, int scale_d) {
    asm volatile(
        "{\n.reg .pred p;\n.reg .b64 db;\n"
        "setp.ne.b32 p, %38, 0;\n"
        "mov.b64 db, {%36, %37};\n"
        "wgmma.mma_async.sync.aligned.m64n64k16.f32.bf16.bf16 "
        "{%0, %1, %2, %3, %4, %5, %6, %7, %8, %9, %10, %11, %12, %13, %14, %15, "
        "%16, %17, %18, %19, %20, %21, %22, %23, %24, %25, %26, %27, %28, %29, %30, %31}, "
        "{%32, %33, %34, %35}, db, p, 1, 1, %39;\n}"
        : "+f"(d[0]), "+f"(d[1]), "+f"(d[2]), "+f"(d[3]), "+f"(d[4]), "+f"(d[5]), "+f"(d[6]), "+f"(d[7]),
          "+f"(d[8]), "+f"(d[9]), "+f"(d[10]), "+f"(d[11]), "+f"(d[12]), "+f"(d[13]), "+f"(d[14]), "+f"(d[15]),
          "+f"(d[16]), "+f"(d[17]), "+f"(d[18]), "+f"(d[19]), "+f"(d[20]), "+f"(d[21]), "+f"(d[22]), "+f"(d[23]),
          "+f"(d[24]), "+f"(d[25]), "+f"(d[26]), "+f"(d[27]), "+f"(d[28]), "+f"(d[29]), "+f"(d[30]), "+f"(d[31])
        : "r"(a[0]), "r"(a[1]), "r"(a[2]), "r"(a[3]), "r"(desc_lo), "r"(desc_hi), "r"(scale_d), "n"(TB));
}
__device__ __forceinline__ void wgmma_pv(float (&d)[64], const uint32_t* a, uint32_t desc_lo, uint32_t desc_hi, int scale_d) {
    asm volatile(
        "{\n.reg .pred p;\n.reg .b64 db;\n"
        "setp.ne.b32 p, %70, 0;\n"
        "mov.b64 db, {%68, %69};\n"
        "wgmma.mma_async.sync.aligned.m64n128k16.f32.bf16.bf16 "
        "{%0, %1, %2, %3, %4, %5, %6, %7, %8, %9, %10, %11, %12, %13, %14, %15, "
        "%16, %17, %18, %19, %20, %21, %22, %23, %24, %25, %26, %27, %28, %29, %30, %31, "
        "%32, %33, %34, %35, %36, %37, %38, %39, %40, %41, %42, %43, %44, %45, %46, %47, "
        "%48, %49, %50, %51, %52, %53, %54, %55, %56, %57, %58, %59, %60, %61, %62, %63}, "
        "{%64, %65, %66, %67}, db, p, 1, 1, 1;\n}"
        : "+f"(d[0]), "+f"(d[1]), "+f"(d[2]), "+f"(d[3]), "+f"(d[4]), "+f"(d[5]), "+f"(d[6]), "+f"(d[7]),
          "+f"(d[8]), "+f"(d[9]), "+f"(d[10]), "+f"(d[11]), "+f"(d[12]), "+f"(d[13]), "+f"(d[14]), "+f"(d[15]),
          "+f"(d[16]), "+f"(d[17]), "+f"(d[18]), "+f"(d[19]), "+f"(d[20]), "+f"(d[21]), "+f"(d[22]), "+f"(d[23]),
          "+f"(d[24]), "+f"(d[25]), "+f"(d[26]), "+f"(d[27]), "+f"(d[28]), "+f"(d[29]), "+f"(d[30]), "+f"(d[31]),
          "+f"(d[32]), "+f"(d[33]), "+f"(d[34]), "+f"(d[35]), "+f"(d[36]), "+f"(d[37]), "+f"(d[38]), "+f"(d[39]),
          "+f"(d[40]), "+f"(d[41]), "+f"(d[42]), "+f"(d[43]), "+f"(d[44]), "+f"(d[45]), "+f"(d[46]), "+f"(d[47]),
          "+f"(d[48]), "+f"(d[49]), "+f"(d[50]), "+f"(d[51]), "+f"(d[52]), "+f"(d[53]), "+f"(d[54]), "+f"(d[55]),
          "+f"(d[56]), "+f"(d[57]), "+f"(d[58]), "+f"(d[59]), "+f"(d[60]), "+f"(d[61]), "+f"(d[62]), "+f"(d[63])
        : "r"(a[0]), "r"(a[1]), "r"(a[2]), "r"(a[3]), "r"(desc_lo), "r"(desc_hi), "r"(scale_d));
}

__device__ __forceinline__ int bcast(int v, int lane, int src) {
    return __reduce_max_sync(~0u, lane == src ? v : 0);
}

__device__ __forceinline__ void sort_pages(const int4& row0, const int4& row1, int first, int n, int lane,
                                           uint32_t s_list, uint32_t s_bits) {
    constexpr int kW = kSortWords / 32;
    const uint32_t e[8] = {(uint32_t)row0.x, (uint32_t)row0.y, (uint32_t)row0.z, (uint32_t)row0.w,
                           (uint32_t)row1.x, (uint32_t)row1.y, (uint32_t)row1.z, (uint32_t)row1.w};
    uint32_t wa[8];
#pragma unroll
    for (int i = 0; i < 8; i++) {
        const bool use = (unsigned)(lane - first + (i >> 2) * 32) < (unsigned)n && e[i] < kSortWords * 32;
        wa[i] = s_bits + (use ? e[i] >> 5 : 0) * 8;
        asm volatile("{\n.reg .pred p;\nsetp.ne.u32 p, %2, 0;\n@p red.shared.or.b32 [%0], %1;\n}"
                     ::"r"(wa[i]), "r"(1u << (e[i] & 31)), "r"((uint32_t)use) : "memory");
    }
    __syncwarp();
    uint32_t cnt[kW + 1];
    cnt[0] = 0;
#pragma unroll
    for (int i = 0; i < kW; i++) {
        uint32_t w;
        asm volatile("ld.shared.b32 %0, [%1];" : "=r"(w) : "r"(s_bits + (lane * kW + i) * 8) : "memory");
        cnt[i + 1] = cnt[i] + __popc(w);
    }
    uint32_t scan = cnt[kW];
#pragma unroll
    for (int o = 1; o < 32; o <<= 1) {
        const uint32_t v = __shfl_up_sync(~0u, scan, o);
        if (lane >= o) scan += v;
    }
    const bool sorted = __shfl_sync(~0u, scan, 31) == (uint32_t)n * 4;
#pragma unroll
    for (int i = 0; i < kW; i++)
        asm volatile("st.shared.b32 [%0], %1;" ::"r"(s_bits + (lane * kW + i) * 8 + 4), "r"(scan - cnt[kW] + cnt[i]) : "memory");
    __syncwarp();
#pragma unroll
    for (int i = 0; i < 8; i++) {
        uint32_t w, base;
        asm volatile("ld.shared.v2.b32 {%0, %1}, [%2];" : "=r"(w), "=r"(base) : "r"(wa[i]) : "memory");
        wa[i] = base + __popc(w & ((1u << (e[i] & 31)) - 1));
    }
#pragma unroll
    for (int i = 0; i < 8; i++) {
        const uint32_t pos = sorted ? wa[i] : (lane - first) * 4 + (i >> 2) * 128 + (i & 3);
        asm volatile("{\n.reg .pred p;\nsetp.ne.u32 p, %2, 0;\n@p st.shared.b32 [%0], %1;\n}"
                     ::"r"(s_list + pos * 4), "r"(e[i] * 2), "r"((uint32_t)((unsigned)(lane - first + (i >> 2) * 32) < (unsigned)n)) : "memory");
    }
}

__device__ unsigned g_progress;

struct Maps {
    CUtensorMap page[2];
    CUtensorMap group[2];
    CUtensorMap vhalf;
    CUtensorMap q;
    CUtensorMap out;
};

struct Ring {
    int slot;
    uint32_t phase;
    __device__ __forceinline__ void advance() {
        if (++slot == kStages) { slot = 0; phase ^= 1; }
    }
};

__global__ void __launch_bounds__(kThreads, 1)
paged_attn_kernel(const int* __restrict__ ctx, const int* __restrict__ table, const __nv_bfloat16* __restrict__ q,
                  __nv_bfloat16* __restrict__ out, unsigned* progress, int oob_coord, float tile_ns,
                  const __grid_constant__ Maps tm) {
    extern __shared__ uint8_t smem_raw[];
    const int tid = threadIdx.x, lane = tid & 31;
    const int b = blockIdx.x / kHkv, h = blockIdx.x % kHkv;
    const int bh = b * kHkv + h;
    const __nv_bfloat16* q_tile = q + (size_t)bh * kRows * kD;
    if (elect_one()) asm volatile("cp.async.bulk.prefetch.L2.global [%0], %1;" ::"l"(q_tile), "r"(16) : "memory");
    if (tid == 0) asm volatile("cp.async.bulk.prefetch.L2.global [%0], %1;" ::"l"(q_tile), "r"(kQPrefetch) : "memory");
    uint32_t t_begin;
    asm volatile("mov.u32 %0, %globaltimer_lo;" : "=r"(t_begin) :: "memory");
    int cl;
    int4 row0, row1;
    if (tid >= 256) {
        const bool head = tid >> 5 == 10;
        const int4* row = reinterpret_cast<const int4*>(table + b * kNBPS) + (head ? 0 : lane);
        row0 = ldg_v4(row);
        asm volatile("ld.global.nc.b32 %0, [%1];" : "=r"(cl) : "l"(ctx + (lane & (kB - 1))) : "memory");
        row1 = ldg_v4(row + (head ? 0 : 32));
    }
    const int warp = __shfl_sync(~0u, tid >> 5, 0);
    const uint32_t sbase = __reduce_max_sync(~0u, (smem_u32(smem_raw) + 1023 + kSmemHead) & ~1023u);
    const uint32_t s_bits = sbase - 4096, s_list = sbase - 2048;
    const uint32_t s_bar = sbase - 1024, s_clock = sbase - 512;
    const uint32_t s_bar_last = s_bar + 32 * kStages;
    static_assert(kStages == 6 && kLead == 4 && kSplit == 3, "barrier layout, code of the last tiles");

    if (warp < 8) {
        if (elect_one()) {
            mbar_init(s_bar + 32 * warp, 1);
            mbar_init(s_bar + 32 * warp + 8, 1);
            mbar_init(s_bar + 32 * warp + 16, warp < kStages ? 9 : 1);
            mbar_init(s_bar + 32 * warp + 24, warp < kStages ? 8 : 1);
            asm volatile("fence.mbarrier_init.release.cluster;" ::: "memory");
            if (warp < 2 || warp >= kStages) {
                mbar_expect_tx(s_bar + 32 * warp, warp < 2 ? kSlotBytes : kSlotBytes / 2);
                mbar_expect_tx(s_bar + 32 * warp + 8, warp < 2 ? kSlotBytes : kSlotBytes / 2);
            }
            if (warp >= kStages) {
                mbar_expect_tx(s_bar + 32 * warp + 16, kSlotBytes / 2);
                mbar_expect_tx(s_bar + 32 * warp + 24, kSlotBytes / 2);
            }
            if (warp == 0) {
                asm volatile("fence.proxy.async.shared::cta;" ::: "memory");
                tma_2d(sbase, &tm.q, s_bar, 0, bh * kRows);
                tma_2d(sbase + kSlotBytes, &tm.q, s_bar + 8, 64, bh * kRows);
            }
        }
    } else if (warp == 8) {
#pragma unroll
        for (int i = 0; i < kSortWords / 32; i++)
            asm volatile("st.shared.b32 [%0], %1;" ::"r"(s_bits + (lane * (kSortWords / 32) + i) * 8), "r"(0) : "memory");
    }
    __syncthreads();

    if (warp >= 8) {
        asm volatile("setmaxnreg.dec.sync.aligned.u32 40;");
        const int kv = (warp >> 1) & 1;
        uint64_t pol;
        asm volatile("createpolicy.fractional.L2::evict_first.b64 %0, 1.0;" : "=l"(pol));
        const int len_l = cl <= 0 ? kSkv : min(cl, kSkv);
        const int len = bcast(len_l, lane, b);
        const int top = (len - 1) / kTileN;
        const int n = max(top, kLead - 1);
        const int early = top > kLead;
        if (warp == 10 && early && elect_one()) {
#pragma unroll
            for (int i = 0; i < 2; i++) {
                const uint32_t dst = sbase + (4 + i) * kSlotBytes, bar = s_bar + 64 + 8 * i;
                mbar_expect_tx(bar, kSlotBytes);
                tma_page(dst, &tm.page[i], bar, h * 2, row0.x * 2, pol);
                tma_page(dst + 4096, &tm.page[i], bar, h * 2, row0.y * 2, pol);
                tma_page(dst + 8192, &tm.page[i], bar, h * 2, row0.z * 2, pol);
                tma_page(dst + 12288, &tm.page[i], bar, h * 2, row0.w * 2, pol);
            }
        }
        if (warp & 1) {
            const int4 src = top < 32 ? row0 : row1;
            const int p0 = bcast(src.x, lane, top & 31) * 2, p1 = bcast(src.y, lane, top & 31) * 2;
            const int p2 = bcast(src.z, lane, top & 31) * 2, p3 = bcast(src.w, lane, top & 31) * 2;
            const int rem = len - top * kTileN, full = (rem - 1) / kPage, r = rem - full * kPage;
            const int last = full == 0 ? p0 : full == 1 ? p1 : full == 2 ? p2 : p3;
            const uint32_t off = (3 - full) * 4096;
            if (elect_one()) {
                const uint32_t dst = sbase + (2 + kv) * kSlotBytes, bar = s_bar + 32 + 8 * kv;
                tma_page(dst + ((off + 4096) & 0x3fff), &tm.page[kv], bar, h * 2, full > 0 ? p0 : oob_coord, pol);
                tma_page(dst + ((off + 8192) & 0x3fff), &tm.page[kv], bar, h * 2, full > 1 ? p1 : oob_coord, pol);
                tma_page(dst + ((off + 12288) & 0x3fff), &tm.page[kv], bar, h * 2, full > 2 ? p2 : oob_coord, pol);
                tma_group(dst + off, &tm.group[kv], bar, r - 16, h * 2, last + 1, pol);
                tma_group(dst + off + 2048, &tm.group[kv], bar, min(r - 8, 0), h * 2, last, pol);
                asm volatile("prefetch.tensormap [%0];" ::"l"(kv ? &tm.vhalf : &tm.out) : "memory");
            }
            {
                __syncwarp();
                asm volatile("bar.sync %0, 192;" ::"r"(2 + kv) : "memory");
                asm volatile("fence.proxy.async.shared::cta;" ::: "memory");
                if (elect_one()) {
                    asm volatile("cp.async.bulk.tensor.2d.global.shared::cta.bulk_group [%0, {%1, %2}], [%3];"
                                 ::"l"(&tm.out), "r"(0), "r"(bh * kRows + kv * 64),
                                 "r"(sbase + ((n + 3) % kStages * 2 + kv) * kSlotBytes) : "memory");
                    asm volatile("cp.async.bulk.commit_group;" ::: "memory");
                }
            }
            asm volatile("cp.async.bulk.wait_group.read 0;" ::: "memory");
            return;
        }
        const int full_l = lane < kB ? (len_l - 1) / kTileN : 0;
        const float t_all = (float)(__reduce_add_sync(~0u, full_l) * kHkv) * tile_ns;
        float origin = (kB * kHkv + __reduce_add_sync(~0u, lane < kB ? len_l - full_l * kTileN : 0) * (1.f / 8)) * tile_ns + kStartLag;
        if (warp == 10) {
            if (lane == 0) {
                const float gain = fminf(__fdividef(kClockGain * t_all, (float)(n * kB * kHkv) * tile_ns), 0.5f);
                mbar_arrive_if(s_bar + 16, true);
                mbar_arrive_if(s_bar + 48, true);
                Ring m{2, 0};
                unsigned g;
#pragma unroll 1
                for (int t = n - 1; t >= kLead - 2; t--) {
                    if (t == kLead - 2) m.advance();
                    mbar_wait(s_bar + 32 * m.slot, m.phase);
                    mbar_arrive_if(s_bar + 32 * m.slot + 16, true);
                    m.advance();
                    uint32_t now;
                    asm volatile("mov.u32 %0, %globaltimer_lo;" : "=r"(now) :: "memory");
                    asm volatile("atom.relaxed.gpu.global.add.u32 %0, [%1], 1;" : "=r"(g) : "l"(progress) : "memory");
                    g &= 0xfffff;
                    const float d = (float)(int)(now - t_begin) - (float)g * tile_ns - origin;
                    if (g >= kClockWarmup) origin = fmaf(fminf(d, kClockStep), gain, origin);
                    asm volatile("st.volatile.shared.b32 [%0], %1;" ::"r"(s_clock), "r"(t_begin + (int)origin) : "memory");
                }
                asm volatile("atom.relaxed.gpu.global.add.u32 %0, [%1], 0x100000;" : "=r"(g) : "l"(progress) : "memory");
                if ((g >> 20) == kB * kHkv - 1) asm volatile("st.relaxed.gpu.global.u32 [%0], 0;" ::"l"(progress) : "memory");
            }
            return;
        }
        asm volatile("st.volatile.shared.b32 [%0], %1;" ::"r"(s_clock), "r"(t_begin + (int)origin) : "memory");
        if (lane < 4 * (kLead - 1)) asm volatile("st.shared.b32 [%0], %1;" ::"r"(s_list + lane * 4), "r"(oob_coord) : "memory");
        sort_pages(row0, row1, early, top - early, lane, s_list, s_bits);
        __syncwarp();
        auto pages = [&](int t) {
            int4 pg;
            asm volatile("ld.shared.v4.b32 {%0, %1, %2, %3}, [%4];" : "=r"(pg.x), "=r"(pg.y), "=r"(pg.z), "=r"(pg.w)
                         : "r"(s_list + t * 16) : "memory");
            return pg;
        };
        const float dt_end = tile_ns * (kB * kHkv / 2);
        const float stagger = dt_end * ((b * 7 % kB) + 0.5f) * (1.f / kB);
        const float dt = __fdividef(t_all - dt_end * (2 * kEvenTiles), (float)(2 * max(n - kEvenTiles, 1)));
        float left = (n > kEvenTiles ? t_all : dt_end * (float)(2 * n)) - stagger;
        auto wait_due = [&](float step, float ahead = 0.f) {
            const int due = (int)(t_all - kWindow - left + fmaxf(fmaf(left, -kTaper / kTaperSpan, kTaper), 0.f) - ahead);
            left -= step;
#pragma unroll 1
            while (true) {
                uint32_t now, org;
                asm volatile("ld.volatile.shared.b32 %0, [%1];" : "=r"(org) : "r"(s_clock) : "memory");
                asm volatile("mov.u32 %0, %globaltimer_lo;" : "=r"(now));
                const int wait = due - (int)(now - org);
                if (wait <= 0) break;
                if (wait > 64) __nanosleep(min(wait >> 1, 200));
            }
        };
        auto acquire = [&](const Ring& r, int kv, float step, float ahead = 0.f) {
            const uint32_t bar = s_bar + 32 * r.slot + 8 * kv;
            mbar_wait(bar + 16, r.phase ^ 1);
            if (lane == 0) mbar_expect_tx(bar, kSlotBytes);
            wait_due(step, ahead);
            return bar;
        };
        auto load4 = [&](uint32_t dst, uint32_t stride, const CUtensorMap* map, uint32_t bar, int c2, const int4& pg) {
            if (elect_one()) {
                tma_page(dst, map, bar, c2, pg.x, pol);
                tma_page(dst + stride, map, bar, c2, pg.y, pol);
                tma_page(dst + 2 * stride, map, bar, c2, pg.z, pol);
                tma_page(dst + 3 * stride, map, bar, c2, pg.w, pol);
            }
        };
        Ring r{2 + early, 0};
        if (early) left -= 2.f * (n > kEvenTiles ? dt : dt_end);
#pragma unroll 1
        for (int t = n - 1 - early; t >= kLead; t--) {
            const int4 pg = pages(t);
            const uint32_t dst = sbase + 2 * r.slot * kSlotBytes;
            const float step = t < kEvenTiles ? dt_end : dt;
            load4(dst, 4096, &tm.page[0], acquire(r, 0, step), h * 2, pg);
            load4(dst + kSlotBytes, 4096, &tm.page[1], acquire(r, 1, step), h * 2, pg);
            r.advance();
        }
        Ring rv = r;
#pragma unroll 1
        for (int i = 0; i < 2 * kLead - kSplit; i++) {
            const int kv = i >= kLead;
            const int t = (kv ? 2 * kLead : kLead) - 1 - i;
            if (t >= n) continue;
            const int4 pg = pages(t);
            const Ring cur = kv ? rv : r;
            load4(sbase + (2 * cur.slot + kv) * kSlotBytes, 4096, &tm.page[kv],
                  acquire(cur, kv, dt_end, kv ? kAheadV : i ? kAheadK : 0.f), h * 2, pg);
            if (kv) rv.advance(); else r.advance();
        }
        left += 0.5f * stagger;
#pragma unroll 1
        for (int j = 0; j < 2 * kSplit; j++) {
            const int half = j >= kSplit, t = (half ? 2 * kSplit : kSplit) - 1 - j;
            const int4 pg = pages(t);
            mbar_wait(s_bar + 32 * rv.slot + 24, rv.phase ^ 1);
            wait_due(0.5f * dt_end, !half || t > 1 ? kAheadV : t ? kAheadR1 : fmaf(stagger, kTightR0, kAheadR0));
            load4(sbase + (2 * rv.slot + 1) * kSlotBytes + (j & 1) * 8192, 2048, &tm.vhalf, s_bar_last + 8 * j, h * 2 + half, pg);
            if (j & 1) rv.advance();
        }
        uint32_t due, now, landed;
        asm volatile("ld.volatile.shared.b32 %0, [%1];" : "=r"(due) : "r"(s_clock) : "memory");
        due += (int)(t_all - kStoreLead + kStoreStagger * stagger);
#pragma unroll 1
        do {
            asm volatile("{\n.reg .pred p;\nmbarrier.test_wait.parity.shared::cta.b64 p, [%1], 0;\nselp.u32 %0, 1, 0, p;\n}"
                         : "=r"(landed) : "r"(s_bar_last + 8 * (2 * kSplit - 2)) : "memory");
            asm volatile("mov.u32 %0, %globaltimer_lo;" : "=r"(now));
        } while (!landed && (int)(due - now) > 0);
        __syncwarp();
        asm volatile("bar.arrive 2, 192;" ::: "memory");
        asm volatile("bar.arrive 3, 192;" ::: "memory");
    } else {
        asm volatile("setmaxnreg.inc.sync.aligned.u32 232;");
        const int wg = warp >> 2;
        const int clb = __reduce_max_sync(~0u, __ldg(ctx + b));
        const int len = clb <= 0 ? kSkv : min(clb, kSkv);
        const int top = (len - 1) / kTileN;
        const float c = clb <= 0 ? 0.f : 0.08838834764831845f * 1.4426950408889634f;

        if (wg == 1) asm volatile("bar.arrive 4, 256;" ::: "memory");
        constexpr uint32_t kDescHi = (2048u >> 4) | (1u << 30);
        constexpr uint32_t kLboK = 1u << 16, kLboV = (1024u >> 4) << 16;
        const uint32_t desc_base = (sbase & 0x3FFFF) >> 4;

        const uint32_t stg = sbase + (max(top, kLead - 1) + 3) % kStages * 2 * kSlotBytes + wg * kSlotBytes + (warp & 3) * 2048;
        const uint32_t st_addr = __shfl_sync(~0u, stg + (lane & 7) * 128 + (((lane >> 3) ^ (lane & 7)) << 4), lane);
        const uint32_t ld_addr = __shfl_sync(~0u, stg + (lane >> 3) * 128 + (((lane & 7) ^ (lane >> 3)) << 4), lane);
        const uint32_t out_off = __shfl_sync(~0u, ((bh * kRows + warp * 16 + (lane >> 3)) * kD + (lane & 7) * 8) * 2, lane);
        float o[64], s[32];
        uint32_t qf[32], p[16];
#pragma unroll
        for (int i = 0; i < 16; i++) p[i] = 0;
#pragma unroll
        for (int i = 0; i < 64; i++) o[i] = 0.f;
#pragma unroll
        for (int i = 0; i < 32; i++) asm volatile("" : "=f"(s[i]));
        float m0 = -1e30f, m1 = -1e30f, n0 = -m0 * c, n1 = n0, l0 = 0.f, l1 = 0.f;
        {
            const int row = wg * 64 + (warp & 3) * 16 + (lane & 7) + ((lane >> 3) & 1) * 8;
#pragma unroll
            for (int half = 0; half < 2; half++) {
                mbar_wait(s_bar + 8 * half, 0);
                const uint32_t base = sbase + half * kSlotBytes + row * 128;
#pragma unroll
                for (int ks = 0; ks < 4; ks++) {
                    const uint32_t addr = base + (((ks * 2 + (lane >> 4)) ^ (lane & 7)) << 4);
                    uint32_t* f = qf + (half * 4 + ks) * 4;
                    asm volatile("ldmatrix.sync.aligned.m8n8.x4.shared.b16 {%0, %1, %2, %3}, [%4];"
                                 : "=r"(f[0]), "=r"(f[1]), "=r"(f[2]), "=r"(f[3]) : "r"(addr) : "memory");
                }
            }
            __syncwarp();
            mbar_arrive_if(s_bar + 16, lane == 0);
        }

        float w0, w1;
        auto exps = [&](uint32_t (&p)[16]) {
            float v0, v1;
#pragma unroll
            for (int i = 0; i < 8; i++) {
                const float e0 = ex2(fmaf(s[4 * i], c, n0)), e1 = ex2(fmaf(s[4 * i + 1], c, n0));
                const float e2 = ex2(fmaf(s[4 * i + 2], c, n1)), e3 = ex2(fmaf(s[4 * i + 3], c, n1));
                w0 = i ? w0 + e0 : e0;
                v0 = i ? v0 + e1 : e1;
                w1 = i ? w1 + e2 : e2;
                v1 = i ? v1 + e3 : e3;
                p[2 * i] = pack_bf16(e0, e1);
                p[2 * i + 1] = pack_bf16(e2, e3);
            }
            w0 += v0;
            w1 += v1;
        };
        auto must_redo = [&](int skip) { return __any_sync(~0u, fmaxf(w0, w1) > kMaxGrowth || skip > 0); };
        auto redo = [&](int skip, uint32_t (&p)[16], auto&& rescale_pending) {
            const int col = (lane & 3) * 2;
            float x0 = m0, x1 = m1;
#pragma unroll
            for (int i = 0; i < 8; i++) {
                if (i * 8 + col < skip) { s[4 * i] = -INFINITY; s[4 * i + 2] = -INFINITY; }
                if (i * 8 + col + 1 < skip) { s[4 * i + 1] = -INFINITY; s[4 * i + 3] = -INFINITY; }
                x0 = fmaxf(x0, fmaxf(s[4 * i], s[4 * i + 1]));
                x1 = fmaxf(x1, fmaxf(s[4 * i + 2], s[4 * i + 3]));
            }
            x0 = fmaxf(x0, __shfl_xor_sync(~0u, x0, 1));
            x1 = fmaxf(x1, __shfl_xor_sync(~0u, x1, 1));
            x0 = fmaxf(x0, __shfl_xor_sync(~0u, x0, 2));
            x1 = fmaxf(x1, __shfl_xor_sync(~0u, x1, 2));
            const float a0 = ex2((m0 - x0) * c), a1 = ex2((m1 - x1) * c);
            m0 = x0;
            m1 = x1;
            n0 = -x0 * c;
            n1 = -x1 * c;
            l0 *= a0;
            l1 *= a1;
#pragma unroll
            for (int i = 0; i < 16; i++) {
                o[4 * i] *= a0;
                o[4 * i + 1] *= a0;
                o[4 * i + 2] *= a1;
                o[4 * i + 3] *= a1;
                rescale_pending(i, i & 1 ? a1 : a0);
            }
            exps(p);
        };
        auto issue_qk = [&](int slot) {
            const uint32_t lo = desc_base + kLboK + slot * (2 * kSlotBytes >> 4);
#pragma unroll
            for (int ks = 0; ks < 8; ks++)
                wgmma_n64<0>(s, qf + ks * 4, lo + (ks >> 2) * 64 + (ks & 3) * 2, kDescHi, ks != 0);
        };
        auto issue_pv = [&](int slot) {
            const uint32_t lo = desc_base + kLboV + (kSlotBytes >> 4) + slot * (2 * kSlotBytes >> 4);
#pragma unroll
            for (int ks = 0; ks < 4; ks++) wgmma_pv(o, p + ks * 4, lo + ks * 256, kDescHi, 1);
        };
        auto turn_begin = [&]() {
            asm volatile("bar.sync %0, 256;" ::"r"(4 + wg) : "memory");
        };
        auto turn_end = [&]() {
            asm volatile("bar.arrive %0, 256;" ::"r"(5 - wg) : "memory");
        };

        Ring rv{0, 0}, r{1, 0};
        int skip = (top + 1) * kTileN - len;
        int t = max(top, kLead - 1);
        fence_regs(qf);
#pragma unroll 1
        do {
            const uint32_t bar_v = s_bar + 32 * rv.slot + 8, bar_k = s_bar + 32 * r.slot;
            fence_regs(s);
            fence_regs(o);
            fence_regs(p);
            mbar_wait(bar_v, rv.phase);
            turn_begin();
            wgmma_fence();
            issue_pv(rv.slot);
            wgmma_commit();
            mbar_wait(bar_k, r.phase);
            wgmma_fence();
            issue_qk(r.slot);
            wgmma_commit();
            turn_end();
            rv = r;
            r.advance();
            wgmma_wait<0>();
            fence_regs(s);
            fence_regs(o);
            fence_regs(p);
            mbar_arrive_if(bar_k + 16, lane == 0);
            mbar_arrive_if(bar_v + 16, lane == 1);
            exps(p);
            if (must_redo(skip)) redo(skip, p, [](int, float) {});
            skip = 0;
            l0 += w0;
            l1 += w1;
        } while (--t >= kLead - 1);
        auto scores = [&](int t, uint32_t (&e)[16], auto&& rescale_pending) {
            fence_regs(s);
            turn_begin();
            mbar_wait(s_bar + 32 * r.slot, r.phase);
            wgmma_fence();
            issue_qk(r.slot);
            wgmma_commit();
            turn_end();
            r.advance();
            wgmma_wait<0>();
            fence_regs(s);
            exps(e);
            if (must_redo(top <= t)) redo(top <= t ? kTileN : 0, e, rescale_pending);
            l0 += w0;
            l1 += w1;
        };
        uint32_t p2[16], p1[16], p0[16];
        scores(2, p2, [&](int i, float a) { scale_bf16(p[i], a); });
        scores(1, p1, [&](int i, float a) { scale_bf16(p[i], a); scale_bf16(p2[i], a); });
        scores(0, p0, [&](int i, float a) { scale_bf16(p[i], a); scale_bf16(p2[i], a); scale_bf16(p1[i], a); });
        fence_regs(o);
        fence_regs(p);
        fence_regs(p2);
        fence_regs(p1);
        fence_regs(p0);
        float oa[32], ob[32];
#pragma unroll
        for (int i = 0; i < 32; i++) {
            asm volatile("mov.b32 %0, %1;" : "=f"(oa[i]) : "f"(o[i]));
            asm volatile("mov.b32 %0, %1;" : "=f"(ob[i]) : "f"(o[32 + i]));
        }
        asm volatile("st.shared.v2.f32 [%0], {%1, %2};" ::"r"(stg + lane * 8), "f"(l0), "f"(l1) : "memory");
        {
            const uint32_t lo = desc_base + (kSlotBytes >> 4) + rv.slot * (2 * kSlotBytes >> 4);
            mbar_wait(s_bar + 32 * rv.slot + 8, rv.phase);
            turn_begin();
            wgmma_fence();
#pragma unroll
            for (int ks = 0; ks < 4; ks++) wgmma_n64<1>(ob, p + ks * 4, lo + 64 + ks * 256, kDescHi, 1);
#pragma unroll
            for (int ks = 0; ks < 4; ks++) wgmma_n64<1>(oa, p + ks * 4, lo + ks * 256, kDescHi, 1);
            wgmma_commit();
            turn_end();
            rv.advance();
        }
        float4 la, lb;
        asm volatile("ld.shared.v4.f32 {%0, %1, %2, %3}, [%4];" : "=f"(la.x), "=f"(la.y), "=f"(la.z), "=f"(la.w)
                     : "r"(stg + (lane >> 2) * 32) : "memory");
        asm volatile("ld.shared.v4.f32 {%0, %1, %2, %3}, [%4];" : "=f"(lb.x), "=f"(lb.y), "=f"(lb.z), "=f"(lb.w)
                     : "r"(stg + (lane >> 2) * 32 + 16) : "memory");
        float i0 = (la.x + la.z) + (lb.x + lb.z), i1 = (la.y + la.w) + (lb.y + lb.w);
        asm("rcp.approx.ftz.f32 %0, %0;" : "+f"(i0));
        asm("rcp.approx.ftz.f32 %0, %0;" : "+f"(i1));
        mbar_arrive_if(s_bar, i0 + i1 < 0.f);
        uint32_t passed;
        auto pv_piece = [&](int j, const uint32_t (&p)[16], float (&d)[32]) {
            const uint32_t lo = desc_base + (kSlotBytes >> 4) + rv.slot * (2 * kSlotBytes >> 4) + (j & 1) * 512;
            mbar_wait(s_bar_last + 8 * j, 0);
            wg1_sync(6 + j, wg);
            wgmma_fence();
#pragma unroll
            for (int ks = 0; ks < 4; ks++)
                wgmma_n64<1>(d, p + ks * 4, lo + ks * 128, (1024u >> 4) | (1u << 30), 1);
            wgmma_commit();
            if (j < 2 * kSplit - 2) wg0_arrive(6 + j, wg);
            if (j == 2 * kSplit - 2)
                asm volatile("{\n.reg .pred p, q;\nmbarrier.test_wait.parity.shared::cta.b64 p, [%1], 0;\n"
                             "vote.sync.any.pred p, p, 0xffffffff;\nsetp.eq.and.u32 q, %2, 0, !p;\n@q bar.arrive %3, 256;\n"
                             "selp.u32 %0, %2, 1, p;\n}" : "=r"(passed) : "r"(s_bar_last + 8 * j + 8), "r"(wg), "r"(6 + j) : "memory");
            if (j == 2 * kSplit - 1) wg0_arrive(5 + j, passed);
            if (j & 1) rv.advance();
        };
        auto stage_rows = [&](int half, int r, const float (&d)[32]) {
            const float a = r ? i1 : i0;
#pragma unroll
            for (int i = 0; i < 2; i++) {
                const float* y = d + 16 * i + 2 * r;
                asm volatile("stmatrix.sync.aligned.m8n8.x4.shared.b16 [%0], {%1, %2, %3, %4};"
                             ::"r"((st_addr ^ (64 * i)) + half * 8192 + r * 1024), "r"(pack_bf16(y[0] * a, y[1] * a)),
                             "r"(pack_bf16(y[4] * a, y[5] * a)), "r"(pack_bf16(y[8] * a, y[9] * a)),
                             "r"(pack_bf16(y[12] * a, y[13] * a)) : "memory");
            }
        };
        pv_piece(0, p2, oa);
        pv_piece(1, p1, oa);
        pv_piece(2, p0, oa);
        wgmma_wait<0>();
        fence_regs(oa);
        stage_rows(0, 0, oa);
        stage_rows(0, 1, oa);
        asm volatile("bar.arrive %0, 192;" ::"r"(2 + wg) : "memory");
        fence_regs(ob);
        pv_piece(3, p2, ob);
        pv_piece(4, p1, ob);
        pv_piece(5, p0, ob);
        wgmma_wait<0>();
        fence_regs(ob);
        char* dst = reinterpret_cast<char*>(out) + out_off;
#pragma unroll
        for (int r = 0; r < 2; r++) {
            stage_rows(1, r, ob);
            if (r == 0) wg0_arrive(5 + 2 * kSplit, wg);
            __syncwarp();
#pragma unroll
            for (int i = 2 * r; i < 2 * r + 2; i++) {
                uint4 v;
                asm volatile("ld.shared.v4.b32 {%0, %1, %2, %3}, [%4];" : "=r"(v.x), "=r"(v.y), "=r"(v.z), "=r"(v.w)
                             : "r"((ld_addr ^ (64 * (i & 1))) + i * 512 + 8192) : "memory");
                asm volatile("st.global.v4.b32 [%0], {%1, %2, %3, %4};" ::"l"(dst + i * 1024 + 128),
                             "r"(v.x), "r"(v.y), "r"(v.z), "r"(v.w) : "memory");
            }
        }
    }
}

typedef CUresult (*EncodeTiledFn)(CUtensorMap*, CUtensorMapDataType, cuuint32_t, void*, const cuuint64_t*,
                                  const cuuint64_t*, const cuuint32_t*, const cuuint32_t*, CUtensorMapInterleave,
                                  CUtensorMapSwizzle, CUtensorMapL2promotion, CUtensorMapFloatOOBfill);

}

extern "C" void kernel_launch(void* const* d_in, const int* in_sizes, int n_in, void* d_out, int out_size) {
    (void)n_in; (void)out_size;
    const int num_phys = in_sizes[1] / (kPage * kHkv * kD);

    static EncodeTiledFn encode = nullptr;
    static unsigned* progress = nullptr;
    static float tile_ns = 0.f;
    if (!encode) {
        int dev = 0, khz = 0, bits = 0;
        cudaGetDevice(&dev);
        cudaDeviceGetAttribute(&khz, cudaDevAttrMemoryClockRate, dev);
        cudaDeviceGetAttribute(&bits, cudaDevAttrGlobalMemoryBusWidth, dev);
        const float peak_gbs = 2.f * (float)khz * (float)(bits / 8) * 1e-6f;
        tile_ns = 2 * kSlotBytes / (kDramEfficiency * (peak_gbs > 0.f ? peak_gbs : 3352.f));
        cudaGetSymbolAddress((void**)&progress, g_progress);
        cudaDriverEntryPointQueryResult qr;
        cudaGetDriverEntryPoint("cuTensorMapEncodeTiled", (void**)&encode, cudaEnableDefault, &qr);
        cudaFuncSetAttribute(paged_attn_kernel, cudaFuncAttributeMaxDynamicSharedMemorySize, kSmemBytes);
    }
    Maps tm;
    auto cache_map = [&](CUtensorMap* map, void* cache, cuuint32_t halves, cuuint32_t groups) {
        const cuuint64_t dim[4] = {64, 8, 2 * kHkv, (cuuint64_t)num_phys * 2};
        const cuuint64_t str[3] = {kHkv * kD * 2, 128, 8 * kHkv * kD * 2};
        const cuuint32_t box[4] = {64, 8, halves, groups};
        const cuuint32_t es[4] = {1, 1, 1, 1};
        encode(map, CU_TENSOR_MAP_DATA_TYPE_BFLOAT16, 4, cache, dim, str, box, es, CU_TENSOR_MAP_INTERLEAVE_NONE,
               CU_TENSOR_MAP_SWIZZLE_128B, CU_TENSOR_MAP_L2_PROMOTION_L2_128B, CU_TENSOR_MAP_FLOAT_OOB_FILL_NONE);
    };
    for (int kv = 0; kv < 2; kv++) {
        cache_map(&tm.page[kv], d_in[1 + kv], 2, 2);
        cache_map(&tm.group[kv], d_in[1 + kv], 2, 1);
    }
    cache_map(&tm.vhalf, d_in[2], 1, 2);
    {
        const cuuint64_t dim[2] = {kD, (cuuint64_t)kB * kHkv * kRows};
        const cuuint64_t str[1] = {kD * 2};
        const cuuint32_t box[2] = {64, kRows};
        const cuuint32_t es[2] = {1, 1};
        encode(&tm.q, CU_TENSOR_MAP_DATA_TYPE_BFLOAT16, 2, d_in[0], dim, str, box, es, CU_TENSOR_MAP_INTERLEAVE_NONE,
               CU_TENSOR_MAP_SWIZZLE_128B, CU_TENSOR_MAP_L2_PROMOTION_L2_128B, CU_TENSOR_MAP_FLOAT_OOB_FILL_NONE);
        const cuuint32_t obox[2] = {64, 64};
        encode(&tm.out, CU_TENSOR_MAP_DATA_TYPE_BFLOAT16, 2, d_out, dim, str, obox, es, CU_TENSOR_MAP_INTERLEAVE_NONE,
               CU_TENSOR_MAP_SWIZZLE_128B, CU_TENSOR_MAP_L2_PROMOTION_NONE, CU_TENSOR_MAP_FLOAT_OOB_FILL_NONE);
    }
    paged_attn_kernel<<<kB * kHkv, kThreads, kSmemBytes>>>(
        (const int*)d_in[4], (const int*)d_in[3], (const __nv_bfloat16*)d_in[0], (__nv_bfloat16*)d_out, progress,
        num_phys * 2, tile_ns, tm);
}
```
